```python
import torch

def _softmax(x, axis=-1):
    return torch.softmax(x, dim=axis)
def _gelu(x):
    return torch.nn.functional.gelu(x, approximate="tanh")
def _silu(x):
    return torch.nn.functional.silu(x)
def _sigmoid(x):
    return torch.sigmoid(x)
def _layernorm(x, axis=-1, eps=1e-5):
    m = x.mean(dim=axis, keepdim=True)
    v = x.var(dim=axis, keepdim=True, unbiased=False)
    return (x - m) / torch.sqrt(v + eps)
def _scatter_add(tgt, idx, src, axis=0):
    return tgt.clone().index_add_(axis, idx, src)
def _segment_sum(src, seg, n):
    out = torch.zeros((n,) + src.shape[1:], dtype=src.dtype)
    return out.index_add_(0, seg, src)
def _pad(x, pw):
    flat = tuple(v for pair in reversed(pw) for v in pair)
    return torch.nn.functional.pad(x, flat)

kernel_name = 'standalone__glu_gated_reglu__prompt'

def setup_inputs():

    _w = (lambda a: (lambda t: t.to(torch.bfloat16) if t.is_floating_point() else t)(torch.as_tensor(a)))
    B, S, D, F = 1, 2048, 576, 4608
    return {
        "x": _w((lambda *s: torch.randn(*s, dtype=torch.bfloat16) * 0.05)(B, S, D)),
        "W_gate": _w((lambda *s: torch.randn(*s, dtype=torch.bfloat16) * 0.05)(D, F) * (2.0 / D) ** 0.5),
        "W_up": _w((lambda *s: torch.randn(*s, dtype=torch.bfloat16) * 0.05)(D, F) * (2.0 / D) ** 0.5),
        "W_down": _w((lambda *s: torch.randn(*s, dtype=torch.bfloat16) * 0.05)(F, D) * (1.0 / F) ** 0.5),
    }

def reference(x, W_gate, W_up, W_down):
    gate = torch.einsum("bsd,df->bsf", x, W_gate)
    up = torch.einsum("bsd,df->bsf", x, W_up)
    gate = gate * (lambda x, dt: x.to(dt))(gate > 0, gate.dtype)
    h = gate * up
    return torch.einsum("bsf,fd->bsd", h, W_down)
```

```cpp
#include <cuda_runtime.h>
#include <cuda_bf16.h>
#include <cuda.h>
#include <stdint.h>

namespace {

constexpr int S_LEN = 2048, D_DIM = 576, F_DIM = 4608;
constexpr int NTHREADS = 384;
#define LEAD1 1
#define LEAD2 2
constexpr uint32_t WGR = 40960;
constexpr uint32_t RB_OFF = 2 * WGR;
constexpr uint32_t ST = 16384;
constexpr uint32_t BAR_OFF = RB_OFF + 9 * ST;
constexpr uint32_t SMEM_BYTES = BAR_OFF + 512 + 1024;
constexpr int B_FULL = 0, B_EMPTY = 9, B_XFULL = 18, B_RFULL = 27, B_RFREE = 29, B_SUM = 31, B_LAND = 35, B_LFREE = 38, B_NBAR = 39;

__device__ uint4 g_part[16 * 8 * 6 * 1024];
__device__ uint4 g_partE[16 * 8 * 1024];
__device__ unsigned int g_flag[16 * 8 * 4 * 32];
#define PROF_H2(i)
#define PROF_C(i)
#define PROF_T(i)
#define PROF_H(i)

__device__ __forceinline__ uint32_t smem_u32(const void* p) { return (uint32_t)__cvta_generic_to_shared(p); }
__device__ __forceinline__ void mbar_init(uint32_t bar, uint32_t cnt) { asm volatile("mbarrier.init.shared::cta.b64 [%0], %1;" ::"r"(bar), "r"(cnt)); }
__device__ __forceinline__ void mbar_expect_tx(uint32_t bar, uint32_t bytes) { asm volatile("mbarrier.arrive.expect_tx.shared::cta.b64 _, [%0], %1;" ::"r"(bar), "r"(bytes) : "memory"); }
__device__ __forceinline__ void mbar_arrive(uint32_t bar) { asm volatile("mbarrier.arrive.shared::cta.b64 _, [%0];" ::"r"(bar) : "memory"); }
__device__ __forceinline__ uint32_t mapa(uint32_t addr, uint32_t cta) { uint32_t r; asm volatile("mapa.shared::cluster.u32 %0, %1, %2;" : "=r"(r) : "r"(addr), "r"(cta)); return r; }
__device__ __forceinline__ void mbar_arrive_remote(uint32_t cluster_addr, uint32_t cnt) { asm volatile("mbarrier.arrive.shared::cluster.b64 _, [%0], %1;" ::"r"(cluster_addr), "r"(cnt) : "memory"); }
__device__ __forceinline__ bool mbar_try_wait(uint32_t bar, uint32_t parity) {
    uint32_t ok;
    asm volatile("{\n.reg .pred p;\nmbarrier.try_wait.parity.shared::cta.b64 p, [%1], %2;\nselp.u32 %0, 1, 0, p;\n}" : "=r"(ok) : "r"(bar), "r"(parity) : "memory");
    return ok;
}
__device__ __forceinline__ bool mbar_test_wait(uint32_t bar, uint32_t parity) {
    uint32_t ok;
    asm volatile("{\n.reg .pred p;\nmbarrier.test_wait.parity.shared::cta.b64 p, [%1], %2;\nselp.u32 %0, 1, 0, p;\n}" : "=r"(ok) : "r"(bar), "r"(parity) : "memory");
    return ok;
}
__device__ __forceinline__ bool mbar_try_wait_cluster(uint32_t bar, uint32_t parity) {
    uint32_t ok;
    asm volatile("{\n.reg .pred p;\nmbarrier.try_wait.parity.acquire.cluster.shared::cta.b64 p, [%1], %2;\nselp.u32 %0, 1, 0, p;\n}" : "=r"(ok) : "r"(bar), "r"(parity) : "memory");
    return ok;
}
__device__ __forceinline__ void mbar_wait(uint32_t bar, uint32_t parity) {
    asm volatile("{\n.reg .pred p;\n.reg .u32 c;\nmov.u32 c, 0;\n"
                 "W_LOOP:\nmbarrier.try_wait.parity.shared::cta.b64 p, [%0], %1;\n@p bra W_DONE;\n"
                 "add.u32 c, c, 1;\nsetp.lt.u32 p, c, 2000000;\n@p bra W_LOOP;\ntrap;\nW_DONE:\n}" ::"r"(bar), "r"(parity) : "memory");
}
__device__ __forceinline__ void mbar_wait_cluster(uint32_t bar, uint32_t parity) {
    asm volatile("{\n.reg .pred p;\n.reg .u32 c;\nmov.u32 c, 0;\n"
                 "W_LOOP:\nmbarrier.try_wait.parity.acquire.cluster.shared::cta.b64 p, [%0], %1;\n@p bra W_DONE;\n"
                 "add.u32 c, c, 1;\nsetp.lt.u32 p, c, 2000000;\n@p bra W_LOOP;\ntrap;\nW_DONE:\n}" ::"r"(bar), "r"(parity) : "memory");
}
__device__ __forceinline__ void flag_wait_reset(unsigned int* flag, uint32_t n) {
    asm volatile("{\n.reg .pred p;\n.reg .u32 c, v;\nmov.u32 c, 0;\n"
                 "W_LOOP:\nld.acquire.gpu.global.u32 v, [%0];\nsetp.ge.u32 p, v, %1;\n@p bra W_DONE;\n"
                 "nanosleep.u32 64;\nadd.u32 c, c, 1;\nsetp.lt.u32 p, c, 4000000;\n@p bra W_LOOP;\ntrap;\nW_DONE:\n"
                 "st.relaxed.gpu.global.u32 [%0], 0;\n}" ::"l"(flag), "r"(n) : "memory");
}
__device__ __forceinline__ void flag_add(unsigned int* flag) {
    asm volatile("red.relaxed.gpu.global.add.u32 [%0], 1;" ::"l"(flag) : "memory");
}
__device__ __forceinline__ void bulk_load(uint32_t saddr, const void* gptr, uint32_t bytes, uint32_t bar) {
    asm volatile("cp.async.bulk.shared::cluster.global.mbarrier::complete_tx::bytes [%0], [%1], %2, [%3];" ::"r"(saddr), "l"(gptr), "r"(bytes), "r"(bar) : "memory");
}
__device__ __forceinline__ void l2_prefetch(const void* gptr, uint32_t bytes) {
    asm volatile("cp.async.bulk.prefetch.L2.global [%0], %1;" ::"l"(gptr), "r"(bytes) : "memory");
}
__device__ __forceinline__ void bulk_store(void* gptr, uint32_t saddr, uint32_t bytes) {
    asm volatile("cp.async.bulk.global.shared::cta.bulk_group [%0], [%1], %2;" ::"l"(gptr), "r"(saddr), "r"(bytes) : "memory");
}
__device__ __forceinline__ void tma_2d(uint32_t dst, const CUtensorMap* m, uint32_t bar, int c0, int c1) {
    asm volatile("cp.async.bulk.tensor.2d.shared::cluster.global.mbarrier::complete_tx::bytes [%0], [%1, {%3, %4}], [%2];"
                 ::"r"(dst), "l"((uint64_t)m), "r"(bar), "r"(c0), "r"(c1) : "memory");
}
__device__ __forceinline__ void tma_2d_mc(uint32_t dst, const CUtensorMap* m, uint32_t bar, int c0, int c1) {
    asm volatile("cp.async.bulk.tensor.2d.shared::cluster.global.mbarrier::complete_tx::bytes.multicast::cluster [%0], [%1, {%3, %4}], [%2], %5;"
                 ::"r"(dst), "l"((uint64_t)m), "r"(bar), "r"(c0), "r"(c1), "h"((uint16_t)3) : "memory");
}
__device__ __forceinline__ uint4 lds128u(uint32_t addr) {
    uint4 v; asm volatile("ld.shared.v4.b32 {%0, %1, %2, %3}, [%4];" : "=r"(v.x), "=r"(v.y), "=r"(v.z), "=r"(v.w) : "r"(addr) : "memory"); return v;
}
__device__ __forceinline__ void tma_store_2d(const CUtensorMap* m, uint32_t src, int c0, int c1) {
    asm volatile("cp.async.bulk.tensor.2d.global.shared::cta.bulk_group [%0, {%2, %3}], [%1];" ::"l"((uint64_t)m), "r"(src), "r"(c0), "r"(c1) : "memory");
}
__device__ __forceinline__ void sts128f(uint32_t addr, float a, float b, float c, float d) {
    asm volatile("st.shared.v4.f32 [%0], {%1, %2, %3, %4};" ::"r"(addr), "f"(a), "f"(b), "f"(c), "f"(d) : "memory");
}
__device__ __forceinline__ void tma_3d(uint32_t dst, const CUtensorMap* m, uint32_t bar, int c0, int c1, int c2) {
    asm volatile("cp.async.bulk.tensor.3d.shared::cluster.global.mbarrier::complete_tx::bytes [%0], [%1, {%3, %4, %5}], [%2];"
                 ::"r"(dst), "l"((uint64_t)m), "r"(bar), "r"(c0), "r"(c1), "r"(c2) : "memory");
}
__device__ __forceinline__ void wg_fence() { asm volatile("wgmma.fence.sync.aligned;" ::: "memory"); }
__device__ __forceinline__ void wg_commit() { asm volatile("wgmma.commit_group.sync.aligned;" ::: "memory"); }
template <int N> __device__ __forceinline__ void wg_wait() { asm volatile("wgmma.wait_group.sync.aligned %0;" ::"n"(N) : "memory"); }
template <int ID, int N> __device__ __forceinline__ void bar_sync() { asm volatile("bar.sync %0, %1;" ::"n"(ID), "n"(N) : "memory"); }
template <int ID, int N> __device__ __forceinline__ void bar_arrive() { asm volatile("bar.arrive %0, %1;" ::"n"(ID), "n"(N) : "memory"); }
__device__ __forceinline__ void wg_bar(uint32_t wg) { if (wg == 0) bar_sync<2, 128>(); else bar_sync<3, 128>(); }
__device__ __forceinline__ void ldsm4(uint32_t addr, uint32_t& a0, uint32_t& a1, uint32_t& a2, uint32_t& a3) {
    asm volatile("ldmatrix.sync.aligned.m8n8.x4.shared.b16 {%0, %1, %2, %3}, [%4];" : "=r"(a0), "=r"(a1), "=r"(a2), "=r"(a3) : "r"(addr) : "memory");
}
__device__ __forceinline__ void stsm4(uint32_t addr, uint32_t a0, uint32_t a1, uint32_t a2, uint32_t a3) {
    asm volatile("stmatrix.sync.aligned.m8n8.x4.shared.b16 [%0], {%1, %2, %3, %4};" ::"r"(addr), "r"(a0), "r"(a1), "r"(a2), "r"(a3) : "memory");
}
__device__ __forceinline__ void sts128(uint32_t addr, uint32_t a0, uint32_t a1, uint32_t a2, uint32_t a3) {
    asm volatile("st.shared.v4.b32 [%0], {%1, %2, %3, %4};" ::"r"(addr), "r"(a0), "r"(a1), "r"(a2), "r"(a3) : "memory");
}
__device__ __forceinline__ void lds128(uint32_t addr, uint32_t& a0, uint32_t& a1, uint32_t& a2, uint32_t& a3) {
    asm volatile("ld.shared.v4.b32 {%0, %1, %2, %3}, [%4];" : "=r"(a0), "=r"(a1), "=r"(a2), "=r"(a3) : "r"(addr) : "memory");
}
__device__ __forceinline__ float4 lds128f(uint32_t addr) {
    float4 v; asm volatile("ld.shared.v4.f32 {%0, %1, %2, %3}, [%4];" : "=f"(v.x), "=f"(v.y), "=f"(v.z), "=f"(v.w) : "r"(addr) : "memory"); return v;
}
__device__ __forceinline__ void st_async4(uint32_t caddr, uint32_t cbar, float a, float b, float c, float d) {
    asm volatile("st.async.weak.shared::cluster.mbarrier::complete_tx::bytes.v4.f32 [%0], {%2, %3, %4, %5}, [%1];"
                 ::"r"(caddr), "r"(cbar), "f"(a), "f"(b), "f"(c), "f"(d) : "memory");
}
__device__ __forceinline__ uint32_t reglu2(float g0, float g1, float u0, float u1) {
    uint32_t gp, up, h;
    asm("cvt.rn.relu.bf16x2.f32 %0, %1, %2;" : "=r"(gp) : "f"(g1), "f"(g0));
    asm("cvt.rn.bf16x2.f32 %0, %1, %2;" : "=r"(up) : "f"(u1), "f"(u0));
    asm("mul.rn.bf16x2 %0, %1, %2;" : "=r"(h) : "r"(gp), "r"(up));
    return h;
}
__device__ __forceinline__ uint32_t pack_bf16(float lo, float hi) {
    uint32_t r; asm("cvt.rn.bf16x2.f32 %0, %1, %2;" : "=r"(r) : "f"(hi), "f"(lo)); return r;
}

__device__ __forceinline__ void wgmma_rs_n128(float (&d)[64], uint32_t a0, uint32_t a1, uint32_t a2, uint32_t a3, uint64_t db, int scale_d) {
  asm volatile("{\n.reg .pred p;\nsetp.ne.b32 p, %69, 0;\nwgmma.mma_async.sync.aligned.m64n128k16.f32.bf16.bf16 {%0, %1, %2, %3, %4, %5, %6, %7, %8, %9, %10, %11, %12, %13, %14, %15, %16, %17, %18, %19, %20, %21, %22, %23, %24, %25, %26, %27, %28, %29, %30, %31, %32, %33, %34, %35, %36, %37, %38, %39, %40, %41, %42, %43, %44, %45, %46, %47, %48, %49, %50, %51, %52, %53, %54, %55, %56, %57, %58, %59, %60, %61, %62, %63}, {%64, %65, %66, %67}, %68, p, 1, 1, 1;\n}"
    : "+f"(d[0]), "+f"(d[1]), "+f"(d[2]), "+f"(d[3]), "+f"(d[4]), "+f"(d[5]), "+f"(d[6]), "+f"(d[7]), "+f"(d[8]), "+f"(d[9]), "+f"(d[10]), "+f"(d[11]), "+f"(d[12]), "+f"(d[13]), "+f"(d[14]), "+f"(d[15]), "+f"(d[16]), "+f"(d[17]), "+f"(d[18]), "+f"(d[19]), "+f"(d[20]), "+f"(d[21]), "+f"(d[22]), "+f"(d[23]), "+f"(d[24]), "+f"(d[25]), "+f"(d[26]), "+f"(d[27]), "+f"(d[28]), "+f"(d[29]), "+f"(d[30]), "+f"(d[31]), "+f"(d[32]), "+f"(d[33]), "+f"(d[34]), "+f"(d[35]), "+f"(d[36]), "+f"(d[37]), "+f"(d[38]), "+f"(d[39]), "+f"(d[40]), "+f"(d[41]), "+f"(d[42]), "+f"(d[43]), "+f"(d[44]), "+f"(d[45]), "+f"(d[46]), "+f"(d[47]), "+f"(d[48]), "+f"(d[49]), "+f"(d[50]), "+f"(d[51]), "+f"(d[52]), "+f"(d[53]), "+f"(d[54]), "+f"(d[55]), "+f"(d[56]), "+f"(d[57]), "+f"(d[58]), "+f"(d[59]), "+f"(d[60]), "+f"(d[61]), "+f"(d[62]), "+f"(d[63])
    : "r"(a0), "r"(a1), "r"(a2), "r"(a3), "l"(db), "r"(scale_d));
}
__device__ __forceinline__ void wgmma_ss_n128(float (&d)[64], uint64_t da, uint64_t db, int scale_d) {
  asm volatile("{\n.reg .pred p;\nsetp.ne.b32 p, %66, 0;\nwgmma.mma_async.sync.aligned.m64n128k16.f32.bf16.bf16 {%0, %1, %2, %3, %4, %5, %6, %7, %8, %9, %10, %11, %12, %13, %14, %15, %16, %17, %18, %19, %20, %21, %22, %23, %24, %25, %26, %27, %28, %29, %30, %31, %32, %33, %34, %35, %36, %37, %38, %39, %40, %41, %42, %43, %44, %45, %46, %47, %48, %49, %50, %51, %52, %53, %54, %55, %56, %57, %58, %59, %60, %61, %62, %63}, %64, %65, p, 1, 1, 0, 1;\n}"
    : "+f"(d[0]), "+f"(d[1]), "+f"(d[2]), "+f"(d[3]), "+f"(d[4]), "+f"(d[5]), "+f"(d[6]), "+f"(d[7]), "+f"(d[8]), "+f"(d[9]), "+f"(d[10]), "+f"(d[11]), "+f"(d[12]), "+f"(d[13]), "+f"(d[14]), "+f"(d[15]), "+f"(d[16]), "+f"(d[17]), "+f"(d[18]), "+f"(d[19]), "+f"(d[20]), "+f"(d[21]), "+f"(d[22]), "+f"(d[23]), "+f"(d[24]), "+f"(d[25]), "+f"(d[26]), "+f"(d[27]), "+f"(d[28]), "+f"(d[29]), "+f"(d[30]), "+f"(d[31]), "+f"(d[32]), "+f"(d[33]), "+f"(d[34]), "+f"(d[35]), "+f"(d[36]), "+f"(d[37]), "+f"(d[38]), "+f"(d[39]), "+f"(d[40]), "+f"(d[41]), "+f"(d[42]), "+f"(d[43]), "+f"(d[44]), "+f"(d[45]), "+f"(d[46]), "+f"(d[47]), "+f"(d[48]), "+f"(d[49]), "+f"(d[50]), "+f"(d[51]), "+f"(d[52]), "+f"(d[53]), "+f"(d[54]), "+f"(d[55]), "+f"(d[56]), "+f"(d[57]), "+f"(d[58]), "+f"(d[59]), "+f"(d[60]), "+f"(d[61]), "+f"(d[62]), "+f"(d[63])
    : "l"(da), "l"(db), "r"(scale_d));
}
__device__ __forceinline__ void wgmma_rs_n64_lo(float (&d)[64], uint32_t a0, uint32_t a1, uint32_t a2, uint32_t a3, uint64_t db, int scale_d) {
  asm volatile("{\n.reg .pred p;\nsetp.ne.b32 p, %37, 0;\nwgmma.mma_async.sync.aligned.m64n64k16.f32.bf16.bf16 {%0, %1, %2, %3, %4, %5, %6, %7, %8, %9, %10, %11, %12, %13, %14, %15, %16, %17, %18, %19, %20, %21, %22, %23, %24, %25, %26, %27, %28, %29, %30, %31}, {%32, %33, %34, %35}, %36, p, 1, 1, 1;\n}"
    : "+f"(d[0]), "+f"(d[1]), "+f"(d[2]), "+f"(d[3]), "+f"(d[4]), "+f"(d[5]), "+f"(d[6]), "+f"(d[7]), "+f"(d[8]), "+f"(d[9]), "+f"(d[10]), "+f"(d[11]), "+f"(d[12]), "+f"(d[13]), "+f"(d[14]), "+f"(d[15]), "+f"(d[16]), "+f"(d[17]), "+f"(d[18]), "+f"(d[19]), "+f"(d[20]), "+f"(d[21]), "+f"(d[22]), "+f"(d[23]), "+f"(d[24]), "+f"(d[25]), "+f"(d[26]), "+f"(d[27]), "+f"(d[28]), "+f"(d[29]), "+f"(d[30]), "+f"(d[31])
    : "r"(a0), "r"(a1), "r"(a2), "r"(a3), "l"(db), "r"(scale_d));
}
__device__ __forceinline__ void wgmma_ss_n64_lo(float (&d)[64], uint64_t da, uint64_t db, int scale_d) {
  asm volatile("{\n.reg .pred p;\nsetp.ne.b32 p, %34, 0;\nwgmma.mma_async.sync.aligned.m64n64k16.f32.bf16.bf16 {%0, %1, %2, %3, %4, %5, %6, %7, %8, %9, %10, %11, %12, %13, %14, %15, %16, %17, %18, %19, %20, %21, %22, %23, %24, %25, %26, %27, %28, %29, %30, %31}, %32, %33, p, 1, 1, 0, 1;\n}"
    : "+f"(d[0]), "+f"(d[1]), "+f"(d[2]), "+f"(d[3]), "+f"(d[4]), "+f"(d[5]), "+f"(d[6]), "+f"(d[7]), "+f"(d[8]), "+f"(d[9]), "+f"(d[10]), "+f"(d[11]), "+f"(d[12]), "+f"(d[13]), "+f"(d[14]), "+f"(d[15]), "+f"(d[16]), "+f"(d[17]), "+f"(d[18]), "+f"(d[19]), "+f"(d[20]), "+f"(d[21]), "+f"(d[22]), "+f"(d[23]), "+f"(d[24]), "+f"(d[25]), "+f"(d[26]), "+f"(d[27]), "+f"(d[28]), "+f"(d[29]), "+f"(d[30]), "+f"(d[31])
    : "l"(da), "l"(db), "r"(scale_d));
}
__device__ __forceinline__ void wgmma_rs_n64_hi(float (&d)[64], uint32_t a0, uint32_t a1, uint32_t a2, uint32_t a3, uint64_t db, int scale_d) {
  asm volatile("{\n.reg .pred p;\nsetp.ne.b32 p, %37, 0;\nwgmma.mma_async.sync.aligned.m64n64k16.f32.bf16.bf16 {%0, %1, %2, %3, %4, %5, %6, %7, %8, %9, %10, %11, %12, %13, %14, %15, %16, %17, %18, %19, %20, %21, %22, %23, %24, %25, %26, %27, %28, %29, %30, %31}, {%32, %33, %34, %35}, %36, p, 1, 1, 1;\n}"
    : "+f"(d[32]), "+f"(d[33]), "+f"(d[34]), "+f"(d[35]), "+f"(d[36]), "+f"(d[37]), "+f"(d[38]), "+f"(d[39]), "+f"(d[40]), "+f"(d[41]), "+f"(d[42]), "+f"(d[43]), "+f"(d[44]), "+f"(d[45]), "+f"(d[46]), "+f"(d[47]), "+f"(d[48]), "+f"(d[49]), "+f"(d[50]), "+f"(d[51]), "+f"(d[52]), "+f"(d[53]), "+f"(d[54]), "+f"(d[55]), "+f"(d[56]), "+f"(d[57]), "+f"(d[58]), "+f"(d[59]), "+f"(d[60]), "+f"(d[61]), "+f"(d[62]), "+f"(d[63])
    : "r"(a0), "r"(a1), "r"(a2), "r"(a3), "l"(db), "r"(scale_d));
}
__device__ __forceinline__ void wgmma_ss_n64_hi(float (&d)[64], uint64_t da, uint64_t db, int scale_d) {
  asm volatile("{\n.reg .pred p;\nsetp.ne.b32 p, %34, 0;\nwgmma.mma_async.sync.aligned.m64n64k16.f32.bf16.bf16 {%0, %1, %2, %3, %4, %5, %6, %7, %8, %9, %10, %11, %12, %13, %14, %15, %16, %17, %18, %19, %20, %21, %22, %23, %24, %25, %26, %27, %28, %29, %30, %31}, %32, %33, p, 1, 1, 0, 1;\n}"
    : "+f"(d[32]), "+f"(d[33]), "+f"(d[34]), "+f"(d[35]), "+f"(d[36]), "+f"(d[37]), "+f"(d[38]), "+f"(d[39]), "+f"(d[40]), "+f"(d[41]), "+f"(d[42]), "+f"(d[43]), "+f"(d[44]), "+f"(d[45]), "+f"(d[46]), "+f"(d[47]), "+f"(d[48]), "+f"(d[49]), "+f"(d[50]), "+f"(d[51]), "+f"(d[52]), "+f"(d[53]), "+f"(d[54]), "+f"(d[55]), "+f"(d[56]), "+f"(d[57]), "+f"(d[58]), "+f"(d[59]), "+f"(d[60]), "+f"(d[61]), "+f"(d[62]), "+f"(d[63])
    : "l"(da), "l"(db), "r"(scale_d));
}

__device__ __forceinline__ uint64_t bdesc(uint32_t addr) {
    uint32_t lo = ((addr & 0x3FFFF) >> 4) | ((8192u >> 4) << 16);
    uint32_t hi = (1024u >> 4) | (1u << 30);
    return ((uint64_t)hi << 32) | lo;
}

__device__ __forceinline__ uint64_t adesc(uint32_t addr) {
    uint32_t lo = ((addr & 0x3FFFF) >> 4) | (1u << 16);
    uint32_t hi = (1024u >> 4) | (1u << 30);
    return ((uint64_t)hi << 32) | lo;
}

struct Ctx {
    uint32_t sb;
    uint32_t s, sprev;
    uint32_t fbits;
    uint32_t wg, warp, lane, tw;
};
#define TIMED(acc_, stmt) stmt
__device__ __forceinline__ uint32_t park_off(uint32_t w, int c) { return c < 4 ? w * WGR + c * 8192 : RB_OFF + w * 32768 + (c - 4) * 8192; }

template <int MODE>
__device__ __forceinline__ void mma_chunk(Ctx& cx, uint32_t (&a)[128], float (&acc)[64]) {
    const uint32_t bars = cx.sb + BAR_OFF;
    const uint32_t priv = cx.warp * 2048 + cx.lane * 16;
    const uint64_t da = adesc(cx.sb + cx.wg * WGR + 32768);
    if (cx.wg == 1) bar_sync<1, 256>();
#pragma unroll
    for (int kb = 0; kb < 9; kb++) {
        if (MODE == 0) {
            mbar_wait(bars + 8 * (B_XFULL + kb), 0);
            PROF_C(2 * kb);
            if (kb < 8) {
                const uint32_t xs = cx.sb + park_off(cx.wg, kb);
                const uint32_t row = cx.warp * 16 + (cx.lane & 15);
#pragma unroll
                for (int k = 0; k < 4; k++) {
                    uint32_t ch = 2 * k + (cx.lane >> 4);
                    ldsm4(xs + row * 128 + ((ch ^ (row & 7)) << 4), a[16 * kb + 4 * k], a[16 * kb + 4 * k + 1], a[16 * kb + 4 * k + 2], a[16 * kb + 4 * k + 3]);
                }
            }
        }
        if (kb == 0) TIMED(cx.wfull, mbar_wait(bars + 8 * (B_FULL + cx.s), (cx.fbits >> cx.s) & 1));
        if (MODE == 0 && kb == 0) PROF_C(20);
        cx.fbits ^= 1u << cx.s;
        const uint64_t db = bdesc(cx.sb + RB_OFF + cx.s * ST);
        const uint32_t sn = cx.s == 8 ? (MODE == 3 ? 2 : 4) : cx.s + 1;
        const uint32_t phn = (cx.fbits >> sn) & 1;
        bool ok = true;
        wg_fence();
        if (kb < 8) {
            wgmma_rs_n128(acc, a[16 * kb + 0], a[16 * kb + 1], a[16 * kb + 2], a[16 * kb + 3], db, kb != 0);
            wgmma_rs_n128(acc, a[16 * kb + 4], a[16 * kb + 5], a[16 * kb + 6], a[16 * kb + 7], db + 128, 1);
        } else {
            wgmma_ss_n128(acc, da, db, 1);
            wgmma_ss_n128(acc, da + 2, db + 128, 1);
        }
        if (MODE != 3) {
            wg_commit();
            if (kb > 0) {
                wg_wait<1>();
                if (cx.tw == 0) mbar_arrive(bars + 8 * (B_EMPTY + cx.sprev));
                if (MODE == 2) {
#pragma unroll
                    for (int k = 0; k < 4; k++)
                        lds128(cx.sb + park_off(cx.wg, kb - 1) + priv + k * 512, a[16 * (kb - 1) + 4 * k], a[16 * (kb - 1) + 4 * k + 1], a[16 * (kb - 1) + 4 * k + 2], a[16 * (kb - 1) + 4 * k + 3]);
                }
            }
        }
        if (kb < 8) {
            ok = mbar_test_wait(bars + 8 * (B_FULL + sn), phn);
            wgmma_rs_n128(acc, a[16 * kb + 8], a[16 * kb + 9], a[16 * kb + 10], a[16 * kb + 11], db + 256, 1);
            wgmma_rs_n128(acc, a[16 * kb + 12], a[16 * kb + 13], a[16 * kb + 14], a[16 * kb + 15], db + 384, 1);
        } else {
            wgmma_ss_n128(acc, da + 4, db + 256, 1);
            wgmma_ss_n128(acc, da + 6, db + 384, 1);
        }
        wg_commit();
        if (kb == (MODE == 3 ? LEAD2 : LEAD1) && cx.wg == 0) bar_arrive<1, 256>();
        if (MODE == 3 && kb > 0) {
            wg_wait<1>();
            if (cx.tw == 0) mbar_arrive(bars + 8 * (B_EMPTY + cx.sprev));
        }
        if (kb < 8) {
            if (!ok) TIMED(cx.wfull, mbar_wait(bars + 8 * (B_FULL + sn), phn));
            if (MODE == 0) PROF_C(2 * kb + 1);
        } else {
            wg_wait<0>();
            if (cx.tw == 0) mbar_arrive(bars + 8 * (B_EMPTY + cx.s));
        }
        cx.sprev = cx.s; cx.s = sn;
    }
}

template <bool LAST>
__device__ __forceinline__ void h_epilogue(Ctx& cx, float (&acc)[64], int c) {
    const uint32_t priv = cx.sb + park_off(cx.wg, c) + cx.warp * 2048 + cx.lane * 16;
    const uint32_t row = cx.warp * 16 + (cx.lane & 15);
#pragma unroll
    for (int k = 0; k < 4; k++) {
        uint32_t h0 = reglu2(acc[8 * k + 0], acc[8 * k + 1], acc[32 + 8 * k + 0], acc[32 + 8 * k + 1]);
        uint32_t h1 = reglu2(acc[8 * k + 2], acc[8 * k + 3], acc[32 + 8 * k + 2], acc[32 + 8 * k + 3]);
        uint32_t h2 = reglu2(acc[8 * k + 4], acc[8 * k + 5], acc[32 + 8 * k + 4], acc[32 + 8 * k + 5]);
        uint32_t h3 = reglu2(acc[8 * k + 6], acc[8 * k + 7], acc[32 + 8 * k + 6], acc[32 + 8 * k + 7]);
        if (LAST) {
            const uint32_t ch = 2 * k + (cx.lane >> 4);
            stsm4(cx.sb + cx.wg * WGR + 32768 + row * 128 + ((ch ^ (row & 7)) << 4), h0, h1, h2, h3);
        } else sts128(priv + k * 512, h0, h1, h2, h3);
    }
    if (LAST) asm volatile("fence.proxy.async.shared::cta;" ::: "memory");
}

__device__ __forceinline__ float bf_lo(uint32_t v) { return __uint_as_float(v << 16); }
__device__ __forceinline__ float bf_hi(uint32_t v) { return __uint_as_float(v & 0xFFFF0000u); }
template <bool FIRST>
__device__ __forceinline__ void add_tiles(float (&acc)[64], uint32_t t0, uint32_t t1) {
#pragma unroll
    for (int p = 0; p < 4; p++) {
        const uint4 u = lds128u(t0 + p * 2048), v = lds128u(t1 + p * 2048);
        const float s[8] = {bf_lo(u.x) + bf_lo(v.x), bf_hi(u.x) + bf_hi(v.x), bf_lo(u.y) + bf_lo(v.y), bf_hi(u.y) + bf_hi(v.y),
                            bf_lo(u.z) + bf_lo(v.z), bf_hi(u.z) + bf_hi(v.z), bf_lo(u.w) + bf_lo(v.w), bf_hi(u.w) + bf_hi(v.w)};
#pragma unroll
        for (int i = 0; i < 8; i++) acc[32 + 8 * p + i] = FIRST ? s[i] : acc[32 + 8 * p + i] + s[i];
    }
}

template <int KIND>
__device__ __forceinline__ void mma_chunk64(Ctx& cx, uint32_t (&a)[128], float (&acc)[64]) {
    const uint32_t bars = cx.sb + BAR_OFF;
    const uint64_t da = adesc(cx.sb + cx.wg * WGR + 32768);
    if (cx.wg == 1) bar_sync<KIND == 1 ? 1 : 5, 256>();
#pragma unroll
    for (int i = 0; i < 5; i++) {
        if (i == 0) TIMED(cx.wfull, mbar_wait(bars + 8 * (B_FULL + cx.s), (cx.fbits >> cx.s) & 1));
        cx.fbits ^= 1u << cx.s;
        const uint64_t db = bdesc(cx.sb + RB_OFF + cx.s * ST);
        const uint32_t sn = cx.s == 8 ? 2 : cx.s + 1;
        const uint32_t phn = (cx.fbits >> sn) & 1;
        bool ok = true;
        wg_fence();
        if (i < 4) {
#pragma unroll
            for (int k = 0; k < 8; k++) {
                if (k == 4) ok = mbar_test_wait(bars + 8 * (B_FULL + sn), phn);
                if (KIND == 2) wgmma_rs_n64_hi(acc, a[32 * i + 4 * k], a[32 * i + 4 * k + 1], a[32 * i + 4 * k + 2], a[32 * i + 4 * k + 3], db + 128 * k, 1);
                else wgmma_rs_n64_lo(acc, a[32 * i + 4 * k], a[32 * i + 4 * k + 1], a[32 * i + 4 * k + 2], a[32 * i + 4 * k + 3], db + 128 * k, (i | k) != 0);
            }
        } else {
#pragma unroll
            for (int k = 0; k < 4; k++) {
                if (KIND == 2) wgmma_ss_n64_hi(acc, da + 2 * k, db + 512 + 128 * k, 1);
                else wgmma_ss_n64_lo(acc, da + 2 * k, db + 512 + 128 * k, 1);
            }
        }
        wg_commit();
        if (i == 1 && cx.wg == 0) bar_arrive<KIND == 1 ? 1 : 5, 256>();
        if (i > 0) {
            wg_wait<1>();
            if (cx.tw == 0) mbar_arrive(bars + 8 * (B_EMPTY + cx.sprev));
        }
        if (i < 4) {
            if (!ok) TIMED(cx.wfull, mbar_wait(bars + 8 * (B_FULL + sn), phn));
        } else {
            if (KIND == 2) TIMED(cx.wother, mbar_wait(bars + 8 * (B_LAND + 2), 0));
            if (KIND == 1) TIMED(cx.wother, mbar_wait_cluster(bars + 8 * (B_RFREE + cx.wg), 0));
            if (KIND == 2) TIMED(cx.wother, mbar_wait_cluster(bars + 8 * (B_RFULL + cx.wg), 0));
            wg_wait<0>();
            if (cx.tw == 0) mbar_arrive(bars + 8 * (B_EMPTY + cx.s));
        }
        cx.sprev = cx.s; cx.s = sn;
    }
}

__device__ __forceinline__ uint32_t xbuf(uint32_t sb, uint32_t w, uint32_t e, uint32_t t) {
    return sb + w * WGR + e * 2048 + t * 16;
}

template <int O, int STRIDE>
__device__ __forceinline__ void emit_atom(const float (&acc)[64], uint4* dst) {
#pragma unroll
    for (int p = 0; p < 4; p++) {
        uint4 v;
        v.x = pack_bf16(acc[O + 8 * p], acc[O + 8 * p + 1]); v.y = pack_bf16(acc[O + 8 * p + 2], acc[O + 8 * p + 3]);
        v.z = pack_bf16(acc[O + 8 * p + 4], acc[O + 8 * p + 5]); v.w = pack_bf16(acc[O + 8 * p + 6], acc[O + 8 * p + 7]);
        __stcg(dst + p * STRIDE, v);
    }
}
__global__ void __cluster_dims__(2, 1, 1) __launch_bounds__(NTHREADS, 1)
reglu_ffn_kernel(const __grid_constant__ CUtensorMap mapX, const __grid_constant__ CUtensorMap mapG, const __grid_constant__ CUtensorMap mapU,
                 const __grid_constant__ CUtensorMap mapD, const __grid_constant__ CUtensorMap mapD1, const __grid_constant__ CUtensorMap mapO,
                 const __nv_bfloat16* __restrict__ wgp, const __nv_bfloat16* __restrict__ wup, const __nv_bfloat16* __restrict__ wd, __nv_bfloat16* __restrict__ out) {
    extern __shared__ uint8_t smem_raw[];
    const uint32_t sb = (smem_u32(smem_raw) + 1023) & ~1023u;
    const uint32_t bars = sb + BAR_OFF;
    const int tid = threadIdx.x;
    const uint32_t wg = __shfl_sync(0xffffffffu, tid >> 7, 0);
    const int r = blockIdx.x & 1, q = (blockIdx.x >> 1) & 3, m = blockIdx.x >> 3;
    const int j = 2 * q + r;

    if (tid == 256) {
        for (int s = 4; s < 9; s++) mbar_init(bars + 8 * (B_FULL + s), 1);
        asm volatile("fence.mbarrier_init.release.cluster;" ::: "memory");
        for (int s = 4; s < 9; s++) {
            const uint32_t fb = bars + 8 * (B_FULL + s);
            mbar_expect_tx(fb, ST);
            tma_2d(sb + RB_OFF + s * ST, &mapG, fb, j * 576, (s - 4) * 64);
            tma_2d(sb + RB_OFF + s * ST + 8192, &mapU, fb, j * 576, (s - 4) * 64);
        }
    } else if (tid == 352) {
        for (int i = 0; i < 9; i++) mbar_init(bars + 8 * (B_XFULL + i), 1);
        asm volatile("fence.mbarrier_init.release.cluster;" ::: "memory");
        for (int i = 0; i < 2; i++) {
            mbar_expect_tx(bars + 8 * (B_XFULL + i), 16384);
            tma_2d(sb + park_off(0, i), &mapX, bars + 8 * (B_XFULL + i), i * 64, m * 128);
            tma_2d(sb + park_off(1, i), &mapX, bars + 8 * (B_XFULL + i), i * 64, m * 128 + 64);
        }
        for (int i = 2; i < 9; i++) mbar_expect_tx(bars + 8 * (B_XFULL + i), 16384);
    } else if (tid < B_NBAR) {
        const int b = tid;
        uint32_t cnt = 0;
        if (b < B_FULL + 4) cnt = 1;
        else if (b >= B_EMPTY && b < B_EMPTY + 9) cnt = 2;
        else if (b >= B_RFULL && b < B_RFULL + 2) cnt = 1;
        else if (b >= B_RFREE && b < B_RFREE + 2) cnt = 2;
        else if (b >= B_SUM && b < B_SUM + 4) cnt = 8;
        else if (b >= B_LAND && b < B_LAND + 3) cnt = 1;
        else if (b == B_LFREE) cnt = 8;
        if (cnt) {
            mbar_init(bars + 8 * b, cnt);
            if (b >= B_RFULL && b < B_RFULL + 2) mbar_expect_tx(bars + 8 * b, 16384);
            asm volatile("fence.mbarrier_init.release.cluster;" ::: "memory");
        }
    }
    __syncthreads();
    asm volatile("barrier.cluster.arrive.release.aligned;" ::: "memory");

    if (wg == 2) {
        asm volatile("setmaxnreg.dec.sync.aligned.u32 56;");
        const int hw = (tid >> 5) & 3, lane = tid & 31;
        if (hw == 0) {
            if (lane == 0) {
                uint32_t s = 4, ebits = 0;
                int c = 0, kb = 5;
                for (int it = 5; it < 81; it++) {
                    mbar_wait(bars + 8 * (B_EMPTY + s), (ebits >> s) & 1);
                    ebits ^= 1u << s;
                    const uint32_t fb = bars + 8 * (B_FULL + s);
                    mbar_expect_tx(fb, ST);
                    tma_2d(sb + RB_OFF + s * ST, &mapG, fb, j * 576 + c * 64, kb * 64);
                    if (++kb == 9) { kb = 0; c++; }
                    s = s == 8 ? 4 : s + 1;
                }
                for (int step = 0; step < 3; step++) {
                    const int ch = (q + 1 + step) & 3;
                    for (kb = 0; kb < 9; kb++) {
                        mbar_wait(bars + 8 * (B_EMPTY + s), (ebits >> s) & 1);
                        ebits ^= 1u << s;
                        const uint32_t fb = bars + 8 * (B_FULL + s);
                        mbar_expect_tx(fb, ST);
                        tma_3d(sb + RB_OFF + s * ST, &mapD, fb, 0, j * 576 + kb * 64, ch * 2);
                        s = s == 8 ? 2 : s + 1;
                    }
                }
                for (int kind = 0; kind < 3; kind++) {
                    const int col = kind == 0 ? 512 : q * 128 + (kind == 1 ? (r ^ 1) : r) * 64;
                    for (int i = 0; i < 5; i++) {
                        mbar_wait(bars + 8 * (B_EMPTY + s), (ebits >> s) & 1);
                        ebits ^= 1u << s;
                        const uint32_t fb = bars + 8 * (B_FULL + s);
                        mbar_expect_tx(fb, ST);
                        tma_2d(sb + RB_OFF + s * ST, &mapD1, fb, col, j * 576 + (i < 4 ? i * 128 : 448));
                        s = s == 8 ? 2 : s + 1;
                    }
                }
            }
            __syncwarp();
            asm volatile("barrier.cluster.wait.acquire.aligned;" ::: "memory");
        } else {
            asm volatile("barrier.cluster.wait.acquire.aligned;" ::: "memory");
            const int wv = hw - 1;
            if (wv < 2) {
                if (lane == 0) {
                    mbar_wait_cluster(bars + 8 * (B_RFREE + 0), 0);
                    mbar_wait_cluster(bars + 8 * (B_RFREE + 1), 0);
                    for (int ph = wv; ph < 3; ph += 2) {
                        flag_wait_reset(&g_flag[((m * 8 + j) * 4 + ph) * 32], 2);
                        PROF_H2(ph * 8);
                        if (ph == 2) mbar_wait(bars + 8 * B_LFREE, 0);
                        asm volatile("fence.proxy.async;" ::: "memory");
                        const uint4* src = g_part + (size_t)((m * 8 + j) * 6 + 2 * ph) * 1024;
                        mbar_expect_tx(bars + 8 * (B_LAND + ph), 32768);
                        if (ph != 1) bulk_load(sb + RB_OFF, src, 32768, bars + 8 * (B_LAND + ph));
                        else {
                            for (int t = 0; t < 4; t++) bulk_load(sb + (t & 1) * WGR + (t >> 1) * 8192, src + t * 512, 8192, bars + 8 * (B_LAND + ph));
                        }
                    }
                    if (wv == 1) flag_wait_reset(&g_flag[((m * 8 + j) * 4 + 3) * 32], 8);
                }
            } else if (lane == 0) {
                for (int kb = 2; kb < 9; kb++)
                    tma_2d_mc(sb + (kb < 8 ? park_off(r, kb) : r * WGR + 32768), &mapX, bars + 8 * (B_XFULL + kb), kb * 64, m * 128 + r * 64);
                uint32_t s = 4, ebits = 0;
                int c = 0, kb = 5;
                for (int it = 5; it < 81; it++) {
                    mbar_wait(bars + 8 * (B_EMPTY + s), (ebits >> s) & 1);
                    ebits ^= 1u << s;
                    tma_2d(sb + RB_OFF + s * ST + 8192, &mapU, bars + 8 * (B_FULL + s), j * 576 + c * 64, kb * 64);
                    if (it < 23) {
                        const size_t o = (size_t)(m * 36 + 2 * (it - 5)) * F_DIM + j * 576 + 128;
                        l2_prefetch(wgp + o, 896); l2_prefetch(wgp + o + F_DIM, 896);
                        l2_prefetch(wup + o, 896); l2_prefetch(wup + o + F_DIM, 896);
                    } else if (it >= 30 && it < 66) l2_prefetch(wd + (size_t)(j * 576 + m * 36 + it - 30) * D_DIM, D_DIM * 2);
                    if (++kb == 9) { kb = 0; c++; }
                    s = s == 8 ? 4 : s + 1;
                }
                for (int ph = 0; ph < 4; ph++) {
                    const int ch = (q + 1 + ph) & 3;
                    mbar_wait(bars + 8 * (B_SUM + ph), 0);
                    PROF_H2(ph * 8 + 4);
                    asm volatile("fence.acq_rel.gpu;" ::: "memory");
                    PROF_H2(ph * 8 + 5);
                    if (ph == 3) {
                        for (int d = 0; d < 8; d++) flag_add(&g_flag[((m * 8 + d) * 4 + 3) * 32]);
                    } else {
                        flag_add(&g_flag[((m * 8 + 2 * ch) * 4 + ph) * 32]);
                        flag_add(&g_flag[((m * 8 + 2 * ch + 1) * 4 + ph) * 32]);
                    }
                }
            }
            __syncwarp();
        }
        {
            bar_sync<6, 128>();
            PROF_H(32);
            const uint4* pe = g_partE + (size_t)(m * 8 + j) * 1024 + hw * 32 + lane;
            uint4 e[8];
#pragma unroll
            for (int k = 0; k < 8; k++) e[k] = __ldcg(pe + k * 128);
            float t[8];
#pragma unroll
            for (int i = 0; i < 8; i++) t[i] = 0.f;
#pragma unroll
            for (int k = 0; k < 8; k++) {
                t[0] += bf_lo(e[k].x); t[1] += bf_hi(e[k].x); t[2] += bf_lo(e[k].y); t[3] += bf_hi(e[k].y);
                t[4] += bf_lo(e[k].z); t[5] += bf_hi(e[k].z); t[6] += bf_lo(e[k].w); t[7] += bf_hi(e[k].w);
            }
            __nv_bfloat16* oe = out + (size_t)(m * 128 + j * 16 + (lane >> 2)) * D_DIM + 512 + (lane & 3) * 2 + hw * 16;
            *reinterpret_cast<uint32_t*>(oe) = pack_bf16(t[0], t[1]);
            *reinterpret_cast<uint32_t*>(oe + 8 * D_DIM) = pack_bf16(t[2], t[3]);
            *reinterpret_cast<uint32_t*>(oe + 8) = pack_bf16(t[4], t[5]);
            *reinterpret_cast<uint32_t*>(oe + 8 + 8 * D_DIM) = pack_bf16(t[6], t[7]);
            PROF_H(33);
        }
        asm volatile("barrier.cluster.arrive.release.aligned;" ::: "memory");
        asm volatile("barrier.cluster.wait.acquire.aligned;" ::: "memory");
    } else {
        asm volatile("setmaxnreg.inc.sync.aligned.u32 224;");
        Ctx cx;
        cx.sb = sb; cx.s = 4; cx.sprev = 4; cx.fbits = 0; cx.wg = wg; cx.warp = (tid >> 5) & 3; cx.lane = tid & 31; cx.tw = tid & 127;
        uint32_t a[128];
        float acc[64];
        PROF_T(0);
        mma_chunk<0>(cx, a, acc);
        h_epilogue<false>(cx, acc, 0);
        PROF_T(1);
        for (int c = 1; c < 8; c++) { mma_chunk<1>(cx, a, acc); h_epilogue<false>(cx, acc, c); PROF_T(1 + c); }
        mma_chunk<2>(cx, a, acc);
        h_epilogue<true>(cx, acc, 8);
        PROF_T(9);
        asm volatile("barrier.cluster.wait.acquire.aligned;" ::: "memory");
        wg_bar(wg);
        if (cx.tw == 0) {
            for (int s = 2; s < 4; s++) mbar_arrive(bars + 8 * (B_EMPTY + s));
            mbar_arrive_remote(mapa(bars + 8 * (B_RFREE + wg), r), 1);
            mbar_arrive_remote(mapa(bars + 8 * (B_RFREE + wg), r ^ 1), 1);
        }
        for (int step = 0; step < 3; step++) {
            mma_chunk<3>(cx, a, acc);
            PROF_T(10 + 2 * step);
            const int ch = (q + 1 + step) & 3;
            uint4* dst = g_part + (size_t)((m * 8 + 2 * ch) * 6 + 2 * step + r) * 1024 + wg * 512 + cx.tw;
            emit_atom<0, 128>(acc, dst);
            emit_atom<32, 128>(acc, dst + 6 * 1024);
            __syncwarp();
            if (cx.lane == 0) mbar_arrive(bars + 8 * (B_SUM + step));
            PROF_T(11 + 2 * step);
        }
        TIMED(cx.wother, mbar_wait(bars + 8 * (B_LAND + 0), 0));
        add_tiles<true>(acc, sb + RB_OFF + wg * 8192 + cx.tw * 16, sb + RB_OFF + 16384 + wg * 8192 + cx.tw * 16);
        __syncwarp();
        if (cx.lane == 0) mbar_arrive(bars + 8 * B_LFREE);
        mma_chunk64<0>(cx, a, acc);
        PROF_T(16);
        emit_atom<0, 32>(acc, g_partE + (size_t)(m * 8 + wg * 4 + cx.warp) * 1024 + j * 128 + cx.lane);
        __syncwarp();
        if (cx.lane == 0) mbar_arrive(bars + 8 * (B_SUM + 3));
        PROF_T(17);
        mma_chunk64<1>(cx, a, acc);
        PROF_T(18);
        {
            const uint32_t rb = mapa(sb, r ^ 1);
            const uint32_t rbar = rb + BAR_OFF + 8 * (B_RFULL + wg);
#pragma unroll
            for (int jj = 0; jj < 8; jj++) st_async4(xbuf(rb, wg, 8 + jj, cx.tw), rbar, acc[4 * jj], acc[4 * jj + 1], acc[4 * jj + 2], acc[4 * jj + 3]);
        }
        TIMED(cx.wother, mbar_wait(bars + 8 * (B_LAND + 1), 0));
        add_tiles<false>(acc, sb + wg * WGR + cx.tw * 16, sb + wg * WGR + 8192 + cx.tw * 16);
        PROF_T(19);
        mma_chunk64<2>(cx, a, acc);
        PROF_T(20);
        {
            const uint32_t ot = sb + wg * WGR + 32768 + cx.warp * 2048;
            const uint32_t row = cx.lane & 15;
#pragma unroll
            for (int p = 0; p < 4; p++) {
                const uint4 u = lds128u(sb + RB_OFF + wg * 8192 + p * 2048 + cx.tw * 16), v = lds128u(sb + RB_OFF + 16384 + wg * 8192 + p * 2048 + cx.tw * 16);
                const float4 n0 = lds128f(xbuf(sb, wg, 8 + 2 * p, cx.tw)), n1 = lds128f(xbuf(sb, wg, 9 + 2 * p, cx.tw));
                const uint32_t h0 = pack_bf16((acc[32 + 8 * p + 0] + n0.x) + (bf_lo(u.x) + bf_lo(v.x)), (acc[32 + 8 * p + 1] + n0.y) + (bf_hi(u.x) + bf_hi(v.x)));
                const uint32_t h1 = pack_bf16((acc[32 + 8 * p + 2] + n0.z) + (bf_lo(u.y) + bf_lo(v.y)), (acc[32 + 8 * p + 3] + n0.w) + (bf_hi(u.y) + bf_hi(v.y)));
                const uint32_t h2 = pack_bf16((acc[32 + 8 * p + 4] + n1.x) + (bf_lo(u.z) + bf_lo(v.z)), (acc[32 + 8 * p + 5] + n1.y) + (bf_hi(u.z) + bf_hi(v.z)));
                const uint32_t h3 = pack_bf16((acc[32 + 8 * p + 6] + n1.z) + (bf_lo(u.w) + bf_lo(v.w)), (acc[32 + 8 * p + 7] + n1.w) + (bf_hi(u.w) + bf_hi(v.w)));
                const uint32_t ch = 2 * p + (cx.lane >> 4);
                stsm4(ot + row * 128 + ((ch ^ (row & 7)) << 4), h0, h1, h2, h3);
            }
            asm volatile("fence.proxy.async.shared::cta;" ::: "memory");
            __syncwarp();
            if (cx.lane == 0) {
                tma_store_2d(&mapO, ot, j * 64, m * 128 + wg * 64 + cx.warp * 16);
                asm volatile("cp.async.bulk.commit_group;" ::: "memory");
                asm volatile("cp.async.bulk.wait_group.read 0;" ::: "memory");
            }
            __syncwarp();
        }
        PROF_T(21); PROF_T(22); PROF_T(23);
        PROF_T(24);
        asm volatile("barrier.cluster.arrive.release.aligned;" ::: "memory");
        asm volatile("barrier.cluster.wait.acquire.aligned;" ::: "memory");
    }
}

typedef CUresult (*EncodeFn)(CUtensorMap*, CUtensorMapDataType, cuuint32_t, void*, const cuuint64_t*, const cuuint64_t*, const cuuint32_t*,
                             const cuuint32_t*, CUtensorMapInterleave, CUtensorMapSwizzle, CUtensorMapL2promotion, CUtensorMapFloatOOBfill);

}

extern "C" void kernel_launch(void* const* d_in, const int* in_sizes, int n_in, void* d_out, int out_size) {
    static EncodeFn enc = nullptr;
    static CUtensorMap mX, mG, mU, mD, mD1, mO;
    static const void* cached[5] = {nullptr, nullptr, nullptr, nullptr, nullptr};
    if (!enc) {
        void* fn = nullptr;
        cudaDriverEntryPointQueryResult st;
        cudaGetDriverEntryPoint("cuTensorMapEncodeTiled", &fn, cudaEnableDefault, &st);
        enc = (EncodeFn)fn;
        cudaFuncSetAttribute(reglu_ffn_kernel, cudaFuncAttributeMaxDynamicSharedMemorySize, SMEM_BYTES);
    }
    if (cached[0] != d_in[0] || cached[1] != d_in[1] || cached[2] != d_in[2] || cached[3] != d_in[3] || cached[4] != d_out) {
        cuuint32_t es[3] = {1, 1, 1};
        {
            cuuint64_t dims[2] = {D_DIM, S_LEN}; cuuint64_t str[1] = {D_DIM * 2}; cuuint32_t box[2] = {64, 64};
            enc(&mX, CU_TENSOR_MAP_DATA_TYPE_BFLOAT16, 2, d_in[0], dims, str, box, es, CU_TENSOR_MAP_INTERLEAVE_NONE, CU_TENSOR_MAP_SWIZZLE_128B, CU_TENSOR_MAP_L2_PROMOTION_L2_256B, CU_TENSOR_MAP_FLOAT_OOB_FILL_NONE);
        }
        {
            cuuint64_t dims[2] = {F_DIM, D_DIM}; cuuint64_t str[1] = {F_DIM * 2}; cuuint32_t box[2] = {64, 64};
            enc(&mG, CU_TENSOR_MAP_DATA_TYPE_BFLOAT16, 2, d_in[1], dims, str, box, es, CU_TENSOR_MAP_INTERLEAVE_NONE, CU_TENSOR_MAP_SWIZZLE_128B, CU_TENSOR_MAP_L2_PROMOTION_L2_256B, CU_TENSOR_MAP_FLOAT_OOB_FILL_NONE);
            enc(&mU, CU_TENSOR_MAP_DATA_TYPE_BFLOAT16, 2, d_in[2], dims, str, box, es, CU_TENSOR_MAP_INTERLEAVE_NONE, CU_TENSOR_MAP_SWIZZLE_128B, CU_TENSOR_MAP_L2_PROMOTION_L2_256B, CU_TENSOR_MAP_FLOAT_OOB_FILL_NONE);
        }
        {
            cuuint64_t dims[3] = {64, F_DIM, 9}; cuuint64_t str[2] = {D_DIM * 2, 128}; cuuint32_t box[3] = {64, 64, 2};
            enc(&mD, CU_TENSOR_MAP_DATA_TYPE_BFLOAT16, 3, d_in[3], dims, str, box, es, CU_TENSOR_MAP_INTERLEAVE_NONE, CU_TENSOR_MAP_SWIZZLE_128B, CU_TENSOR_MAP_L2_PROMOTION_L2_256B, CU_TENSOR_MAP_FLOAT_OOB_FILL_NONE);
            cuuint64_t dims1[2] = {D_DIM, F_DIM}; cuuint64_t str1[1] = {D_DIM * 2}; cuuint32_t box1[2] = {64, 128};
            enc(&mD1, CU_TENSOR_MAP_DATA_TYPE_BFLOAT16, 2, d_in[3], dims1, str1, box1, es, CU_TENSOR_MAP_INTERLEAVE_NONE, CU_TENSOR_MAP_SWIZZLE_128B, CU_TENSOR_MAP_L2_PROMOTION_L2_256B, CU_TENSOR_MAP_FLOAT_OOB_FILL_NONE);
        }
        {
            cuuint64_t dims[2] = {D_DIM, S_LEN}; cuuint64_t str[1] = {D_DIM * 2}; cuuint32_t box[2] = {64, 16};
            enc(&mO, CU_TENSOR_MAP_DATA_TYPE_BFLOAT16, 2, d_out, dims, str, box, es, CU_TENSOR_MAP_INTERLEAVE_NONE, CU_TENSOR_MAP_SWIZZLE_128B, CU_TENSOR_MAP_L2_PROMOTION_NONE, CU_TENSOR_MAP_FLOAT_OOB_FILL_NONE);
        }
        for (int i = 0; i < 4; i++) cached[i] = d_in[i];
        cached[4] = d_out;
    }
    reglu_ffn_kernel<<<128, NTHREADS, SMEM_BYTES>>>(mX, mG, mU, mD, mD1, mO, (const __nv_bfloat16*)d_in[1], (const __nv_bfloat16*)d_in[2], (const __nv_bfloat16*)d_in[3], (__nv_bfloat16*)d_out);
}
```

```cpp
#include <cuda_runtime.h>
#include <cuda_bf16.h>
#include <cuda.h>
#include <stdint.h>

namespace {

constexpr int S_LEN = 2048, D_DIM = 576, F_DIM = 4608;
constexpr int NTHREADS = 384;
constexpr int LAG0 = 3, LAG1 = 2, LAG2 = 3, STAG64 = 3;
constexpr uint32_t WGR = 40960;
constexpr uint32_t RB_OFF = 2 * WGR;
constexpr uint32_t ST = 16384;
constexpr uint32_t BAR_OFF = RB_OFF + 9 * ST;
constexpr uint32_t SMEM_BYTES = BAR_OFF + 512 + 1024;
constexpr uint32_t TAG_OFF = BAR_OFF + 384;
constexpr int B_FULL = 0, B_EMPTY = 9, B_XFULL = 18, B_RFULL = 27, B_RFREE = 29, B_PFREE = 31, B_STG = 32, B_SFREE = 40, B_LAND = 42,
              B_LFREE = 45, B_TAG = 46;

__device__ uint4 g_part[16 * 8 * 6 * 1024];
__device__ uint4 g_partE[16 * 8 * 1024];
__device__ unsigned int g_epoch[128];
__device__ unsigned int g_flag[16 * 8 * 4 * 32];

__device__ __forceinline__ uint32_t smem_u32(const void* p) { return (uint32_t)__cvta_generic_to_shared(p); }
__device__ __forceinline__ void mbar_init(uint32_t bar, uint32_t cnt) { asm volatile("mbarrier.init.shared::cta.b64 [%0], %1;" ::"r"(bar), "r"(cnt)); }
__device__ __forceinline__ void mbar_expect_tx(uint32_t bar, uint32_t bytes) { asm volatile("mbarrier.arrive.expect_tx.shared::cta.b64 _, [%0], %1;" ::"r"(bar), "r"(bytes) : "memory"); }
__device__ __forceinline__ void mbar_arrive(uint32_t bar) { asm volatile("mbarrier.arrive.shared::cta.b64 _, [%0];" ::"r"(bar) : "memory"); }
__device__ __forceinline__ uint32_t mapa(uint32_t addr, uint32_t cta) { uint32_t r; asm volatile("mapa.shared::cluster.u32 %0, %1, %2;" : "=r"(r) : "r"(addr), "r"(cta)); return r; }
__device__ __forceinline__ void mbar_arrive_remote(uint32_t cluster_addr, uint32_t cnt) { asm volatile("mbarrier.arrive.shared::cluster.b64 _, [%0], %1;" ::"r"(cluster_addr), "r"(cnt) : "memory"); }
__device__ __forceinline__ bool mbar_test_wait(uint32_t bar, uint32_t parity) {
    uint32_t ok;
    asm volatile("{\n.reg .pred p;\nmbarrier.test_wait.parity.shared::cta.b64 p, [%1], %2;\nselp.u32 %0, 1, 0, p;\n}" : "=r"(ok) : "r"(bar), "r"(parity) : "memory");
    return ok;
}
__device__ __forceinline__ void mbar_wait(uint32_t bar, uint32_t parity) {
    asm volatile("{\n.reg .pred p;\n.reg .u32 c;\nmov.u32 c, 0;\n"
                 "W_LOOP:\nmbarrier.try_wait.parity.shared::cta.b64 p, [%0], %1;\n@p bra W_DONE;\n"
                 "add.u32 c, c, 1;\nsetp.lt.u32 p, c, 2000000;\n@p bra W_LOOP;\ntrap;\nW_DONE:\n}" ::"r"(bar), "r"(parity) : "memory");
}
__device__ __forceinline__ void mbar_wait_cluster(uint32_t bar, uint32_t parity) {
    asm volatile("{\n.reg .pred p;\n.reg .u32 c;\nmov.u32 c, 0;\n"
                 "W_LOOP:\nmbarrier.try_wait.parity.acquire.cluster.shared::cta.b64 p, [%0], %1;\n@p bra W_DONE;\n"
                 "add.u32 c, c, 1;\nsetp.lt.u32 p, c, 2000000;\n@p bra W_LOOP;\ntrap;\nW_DONE:\n}" ::"r"(bar), "r"(parity) : "memory");
}
__device__ __forceinline__ void flag_wait_reset(unsigned int* flag, uint32_t n) {
    asm volatile("{\n.reg .pred p;\n.reg .u32 c, v;\nmov.u32 c, 0;\n"
                 "W_LOOP:\nld.acquire.gpu.global.u32 v, [%0];\nsetp.ge.u32 p, v, %1;\n@p bra W_DONE;\n"
                 "nanosleep.u32 64;\nadd.u32 c, c, 1;\nsetp.lt.u32 p, c, 4000000;\n@p bra W_LOOP;\ntrap;\nW_DONE:\n"
                 "st.relaxed.gpu.global.u32 [%0], 0;\n}" ::"l"(flag), "r"(n) : "memory");
}
__device__ __forceinline__ void flag_add(unsigned int* flag) {
    asm volatile("red.relaxed.gpu.global.add.u32 [%0], 1;" ::"l"(flag) : "memory");
}
__device__ __forceinline__ void bulk_load(uint32_t saddr, const void* gptr, uint32_t bytes, uint32_t bar) {
    asm volatile("cp.async.bulk.shared::cluster.global.mbarrier::complete_tx::bytes [%0], [%1], %2, [%3];" ::"r"(saddr), "l"(gptr), "r"(bytes), "r"(bar) : "memory");
}
__device__ __forceinline__ void tma_prefetch_2d(const CUtensorMap* m, int c0, int c1) {
    asm volatile("cp.async.bulk.prefetch.tensor.2d.L2.global [%0, {%1, %2}];" ::"l"((uint64_t)m), "r"(c0), "r"(c1) : "memory");
}
__device__ __forceinline__ void prefetch_map(const CUtensorMap* m) { asm volatile("prefetch.tensormap [%0];" ::"l"((uint64_t)m) : "memory"); }
__device__ __forceinline__ void l2_prefetch(const void* gptr, uint32_t bytes) {
    asm volatile("cp.async.bulk.prefetch.L2.global [%0], %1;" ::"l"(gptr), "r"(bytes) : "memory");
}
__device__ __forceinline__ void bulk_store(void* gptr, uint32_t saddr, uint32_t bytes) {
    asm volatile("cp.async.bulk.global.shared::cta.bulk_group [%0], [%1], %2;" ::"l"(gptr), "r"(saddr), "r"(bytes) : "memory");
}
__device__ __forceinline__ void tma_2d(uint32_t dst, const CUtensorMap* m, uint32_t bar, int c0, int c1) {
    asm volatile("cp.async.bulk.tensor.2d.shared::cluster.global.mbarrier::complete_tx::bytes [%0], [%1, {%3, %4}], [%2];"
                 ::"r"(dst), "l"((uint64_t)m), "r"(bar), "r"(c0), "r"(c1) : "memory");
}
__device__ __forceinline__ void tma_2d_mc(uint32_t dst, const CUtensorMap* m, uint32_t bar, int c0, int c1) {
    asm volatile("cp.async.bulk.tensor.2d.shared::cluster.global.mbarrier::complete_tx::bytes.multicast::cluster [%0], [%1, {%3, %4}], [%2], %5;"
                 ::"r"(dst), "l"((uint64_t)m), "r"(bar), "r"(c0), "r"(c1), "h"((uint16_t)3) : "memory");
}
__device__ __forceinline__ uint4 lds128u(uint32_t addr) {
    uint4 v; asm volatile("ld.shared.v4.b32 {%0, %1, %2, %3}, [%4];" : "=r"(v.x), "=r"(v.y), "=r"(v.z), "=r"(v.w) : "r"(addr) : "memory"); return v;
}
__device__ __forceinline__ void tma_3d(uint32_t dst, const CUtensorMap* m, uint32_t bar, int c0, int c1, int c2) {
    asm volatile("cp.async.bulk.tensor.3d.shared::cluster.global.mbarrier::complete_tx::bytes [%0], [%1, {%3, %4, %5}], [%2];"
                 ::"r"(dst), "l"((uint64_t)m), "r"(bar), "r"(c0), "r"(c1), "r"(c2) : "memory");
}
__device__ __forceinline__ void wg_fence() { asm volatile("wgmma.fence.sync.aligned;" ::: "memory"); }
__device__ __forceinline__ void wg_commit() { asm volatile("wgmma.commit_group.sync.aligned;" ::: "memory"); }
template <int N> __device__ __forceinline__ void wg_wait() { asm volatile("wgmma.wait_group.sync.aligned %0;" ::"n"(N) : "memory"); }
template <int ID, int N> __device__ __forceinline__ void bar_sync() { asm volatile("bar.sync %0, %1;" ::"n"(ID), "n"(N) : "memory"); }
template <int ID, int N> __device__ __forceinline__ void bar_arrive() { asm volatile("bar.arrive %0, %1;" ::"n"(ID), "n"(N) : "memory"); }
__device__ __forceinline__ void ldsm4(uint32_t addr, uint32_t& a0, uint32_t& a1, uint32_t& a2, uint32_t& a3) {
    asm volatile("ldmatrix.sync.aligned.m8n8.x4.shared.b16 {%0, %1, %2, %3}, [%4];" : "=r"(a0), "=r"(a1), "=r"(a2), "=r"(a3) : "r"(addr) : "memory");
}
__device__ __forceinline__ void stsm4(uint32_t addr, uint32_t a0, uint32_t a1, uint32_t a2, uint32_t a3) {
    asm volatile("stmatrix.sync.aligned.m8n8.x4.shared.b16 [%0], {%1, %2, %3, %4};" ::"r"(addr), "r"(a0), "r"(a1), "r"(a2), "r"(a3) : "memory");
}
__device__ __forceinline__ void sts128(uint32_t addr, uint32_t a0, uint32_t a1, uint32_t a2, uint32_t a3) {
    asm volatile("st.shared.v4.b32 [%0], {%1, %2, %3, %4};" ::"r"(addr), "r"(a0), "r"(a1), "r"(a2), "r"(a3) : "memory");
}
__device__ __forceinline__ void lds128(uint32_t addr, uint32_t& a0, uint32_t& a1, uint32_t& a2, uint32_t& a3) {
    asm volatile("ld.shared.v4.b32 {%0, %1, %2, %3}, [%4];" : "=r"(a0), "=r"(a1), "=r"(a2), "=r"(a3) : "r"(addr) : "memory");
}
__device__ __forceinline__ float4 lds128f(uint32_t addr) {
    float4 v; asm volatile("ld.shared.v4.f32 {%0, %1, %2, %3}, [%4];" : "=f"(v.x), "=f"(v.y), "=f"(v.z), "=f"(v.w) : "r"(addr) : "memory"); return v;
}
__device__ __forceinline__ void st_async4(uint32_t caddr, uint32_t cbar, float a, float b, float c, float d) {
    asm volatile("st.async.weak.shared::cluster.mbarrier::complete_tx::bytes.v4.f32 [%0], {%2, %3, %4, %5}, [%1];"
                 ::"r"(caddr), "r"(cbar), "f"(a), "f"(b), "f"(c), "f"(d) : "memory");
}
__device__ __forceinline__ uint32_t reglu2(float g0, float g1, float u0, float u1) {
    uint32_t gp, up, h;
    asm("cvt.rn.relu.bf16x2.f32 %0, %1, %2;" : "=r"(gp) : "f"(g1), "f"(g0));
    asm("cvt.rn.bf16x2.f32 %0, %1, %2;" : "=r"(up) : "f"(u1), "f"(u0));
    asm("mul.rn.bf16x2 %0, %1, %2;" : "=r"(h) : "r"(gp), "r"(up));
    return h;
}
__device__ __forceinline__ uint32_t pack_bf16(float lo, float hi) {
    uint32_t r; asm("cvt.rn.bf16x2.f32 %0, %1, %2;" : "=r"(r) : "f"(hi), "f"(lo)); return r;
}

__device__ __forceinline__ void wgmma_rs_n128(float (&d)[64], uint32_t a0, uint32_t a1, uint32_t a2, uint32_t a3, uint64_t db, int scale_d) {
  asm volatile("{\n.reg .pred p;\nsetp.ne.b32 p, %69, 0;\nwgmma.mma_async.sync.aligned.m64n128k16.f32.bf16.bf16 {%0, %1, %2, %3, %4, %5, %6, %7, %8, %9, %10, %11, %12, %13, %14, %15, %16, %17, %18, %19, %20, %21, %22, %23, %24, %25, %26, %27, %28, %29, %30, %31, %32, %33, %34, %35, %36, %37, %38, %39, %40, %41, %42, %43, %44, %45, %46, %47, %48, %49, %50, %51, %52, %53, %54, %55, %56, %57, %58, %59, %60, %61, %62, %63}, {%64, %65, %66, %67}, %68, p, 1, 1, 1;\n}"
    : "+f"(d[0]), "+f"(d[1]), "+f"(d[2]), "+f"(d[3]), "+f"(d[4]), "+f"(d[5]), "+f"(d[6]), "+f"(d[7]), "+f"(d[8]), "+f"(d[9]), "+f"(d[10]), "+f"(d[11]), "+f"(d[12]), "+f"(d[13]), "+f"(d[14]), "+f"(d[15]), "+f"(d[16]), "+f"(d[17]), "+f"(d[18]), "+f"(d[19]), "+f"(d[20]), "+f"(d[21]), "+f"(d[22]), "+f"(d[23]), "+f"(d[24]), "+f"(d[25]), "+f"(d[26]), "+f"(d[27]), "+f"(d[28]), "+f"(d[29]), "+f"(d[30]), "+f"(d[31]), "+f"(d[32]), "+f"(d[33]), "+f"(d[34]), "+f"(d[35]), "+f"(d[36]), "+f"(d[37]), "+f"(d[38]), "+f"(d[39]), "+f"(d[40]), "+f"(d[41]), "+f"(d[42]), "+f"(d[43]), "+f"(d[44]), "+f"(d[45]), "+f"(d[46]), "+f"(d[47]), "+f"(d[48]), "+f"(d[49]), "+f"(d[50]), "+f"(d[51]), "+f"(d[52]), "+f"(d[53]), "+f"(d[54]), "+f"(d[55]), "+f"(d[56]), "+f"(d[57]), "+f"(d[58]), "+f"(d[59]), "+f"(d[60]), "+f"(d[61]), "+f"(d[62]), "+f"(d[63])
    : "r"(a0), "r"(a1), "r"(a2), "r"(a3), "l"(db), "r"(scale_d));
}
__device__ __forceinline__ void wgmma_ss_n128(float (&d)[64], uint64_t da, uint64_t db, int scale_d) {
  asm volatile("{\n.reg .pred p;\nsetp.ne.b32 p, %66, 0;\nwgmma.mma_async.sync.aligned.m64n128k16.f32.bf16.bf16 {%0, %1, %2, %3, %4, %5, %6, %7, %8, %9, %10, %11, %12, %13, %14, %15, %16, %17, %18, %19, %20, %21, %22, %23, %24, %25, %26, %27, %28, %29, %30, %31, %32, %33, %34, %35, %36, %37, %38, %39, %40, %41, %42, %43, %44, %45, %46, %47, %48, %49, %50, %51, %52, %53, %54, %55, %56, %57, %58, %59, %60, %61, %62, %63}, %64, %65, p, 1, 1, 0, 1;\n}"
    : "+f"(d[0]), "+f"(d[1]), "+f"(d[2]), "+f"(d[3]), "+f"(d[4]), "+f"(d[5]), "+f"(d[6]), "+f"(d[7]), "+f"(d[8]), "+f"(d[9]), "+f"(d[10]), "+f"(d[11]), "+f"(d[12]), "+f"(d[13]), "+f"(d[14]), "+f"(d[15]), "+f"(d[16]), "+f"(d[17]), "+f"(d[18]), "+f"(d[19]), "+f"(d[20]), "+f"(d[21]), "+f"(d[22]), "+f"(d[23]), "+f"(d[24]), "+f"(d[25]), "+f"(d[26]), "+f"(d[27]), "+f"(d[28]), "+f"(d[29]), "+f"(d[30]), "+f"(d[31]), "+f"(d[32]), "+f"(d[33]), "+f"(d[34]), "+f"(d[35]), "+f"(d[36]), "+f"(d[37]), "+f"(d[38]), "+f"(d[39]), "+f"(d[40]), "+f"(d[41]), "+f"(d[42]), "+f"(d[43]), "+f"(d[44]), "+f"(d[45]), "+f"(d[46]), "+f"(d[47]), "+f"(d[48]), "+f"(d[49]), "+f"(d[50]), "+f"(d[51]), "+f"(d[52]), "+f"(d[53]), "+f"(d[54]), "+f"(d[55]), "+f"(d[56]), "+f"(d[57]), "+f"(d[58]), "+f"(d[59]), "+f"(d[60]), "+f"(d[61]), "+f"(d[62]), "+f"(d[63])
    : "l"(da), "l"(db), "r"(scale_d));
}
__device__ __forceinline__ void wgmma_rs_n64_lo(float (&d)[64], uint32_t a0, uint32_t a1, uint32_t a2, uint32_t a3, uint64_t db, int scale_d) {
  asm volatile("{\n.reg .pred p;\nsetp.ne.b32 p, %37, 0;\nwgmma.mma_async.sync.aligned.m64n64k16.f32.bf16.bf16 {%0, %1, %2, %3, %4, %5, %6, %7, %8, %9, %10, %11, %12, %13, %14, %15, %16, %17, %18, %19, %20, %21, %22, %23, %24, %25, %26, %27, %28, %29, %30, %31}, {%32, %33, %34, %35}, %36, p, 1, 1, 1;\n}"
    : "+f"(d[0]), "+f"(d[1]), "+f"(d[2]), "+f"(d[3]), "+f"(d[4]), "+f"(d[5]), "+f"(d[6]), "+f"(d[7]), "+f"(d[8]), "+f"(d[9]), "+f"(d[10]), "+f"(d[11]), "+f"(d[12]), "+f"(d[13]), "+f"(d[14]), "+f"(d[15]), "+f"(d[16]), "+f"(d[17]), "+f"(d[18]), "+f"(d[19]), "+f"(d[20]), "+f"(d[21]), "+f"(d[22]), "+f"(d[23]), "+f"(d[24]), "+f"(d[25]), "+f"(d[26]), "+f"(d[27]), "+f"(d[28]), "+f"(d[29]), "+f"(d[30]), "+f"(d[31])
    : "r"(a0), "r"(a1), "r"(a2), "r"(a3), "l"(db), "r"(scale_d));
}
__device__ __forceinline__ void wgmma_ss_n64_lo(float (&d)[64], uint64_t da, uint64_t db, int scale_d) {
  asm volatile("{\n.reg .pred p;\nsetp.ne.b32 p, %34, 0;\nwgmma.mma_async.sync.aligned.m64n64k16.f32.bf16.bf16 {%0, %1, %2, %3, %4, %5, %6, %7, %8, %9, %10, %11, %12, %13, %14, %15, %16, %17, %18, %19, %20, %21, %22, %23, %24, %25, %26, %27, %28, %29, %30, %31}, %32, %33, p, 1, 1, 0, 1;\n}"
    : "+f"(d[0]), "+f"(d[1]), "+f"(d[2]), "+f"(d[3]), "+f"(d[4]), "+f"(d[5]), "+f"(d[6]), "+f"(d[7]), "+f"(d[8]), "+f"(d[9]), "+f"(d[10]), "+f"(d[11]), "+f"(d[12]), "+f"(d[13]), "+f"(d[14]), "+f"(d[15]), "+f"(d[16]), "+f"(d[17]), "+f"(d[18]), "+f"(d[19]), "+f"(d[20]), "+f"(d[21]), "+f"(d[22]), "+f"(d[23]), "+f"(d[24]), "+f"(d[25]), "+f"(d[26]), "+f"(d[27]), "+f"(d[28]), "+f"(d[29]), "+f"(d[30]), "+f"(d[31])
    : "l"(da), "l"(db), "r"(scale_d));
}
__device__ __forceinline__ void wgmma_rs_n64_hi(float (&d)[64], uint32_t a0, uint32_t a1, uint32_t a2, uint32_t a3, uint64_t db, int scale_d) {
  asm volatile("{\n.reg .pred p;\nsetp.ne.b32 p, %37, 0;\nwgmma.mma_async.sync.aligned.m64n64k16.f32.bf16.bf16 {%0, %1, %2, %3, %4, %5, %6, %7, %8, %9, %10, %11, %12, %13, %14, %15, %16, %17, %18, %19, %20, %21, %22, %23, %24, %25, %26, %27, %28, %29, %30, %31}, {%32, %33, %34, %35}, %36, p, 1, 1, 1;\n}"
    : "+f"(d[32]), "+f"(d[33]), "+f"(d[34]), "+f"(d[35]), "+f"(d[36]), "+f"(d[37]), "+f"(d[38]), "+f"(d[39]), "+f"(d[40]), "+f"(d[41]), "+f"(d[42]), "+f"(d[43]), "+f"(d[44]), "+f"(d[45]), "+f"(d[46]), "+f"(d[47]), "+f"(d[48]), "+f"(d[49]), "+f"(d[50]), "+f"(d[51]), "+f"(d[52]), "+f"(d[53]), "+f"(d[54]), "+f"(d[55]), "+f"(d[56]), "+f"(d[57]), "+f"(d[58]), "+f"(d[59]), "+f"(d[60]), "+f"(d[61]), "+f"(d[62]), "+f"(d[63])
    : "r"(a0), "r"(a1), "r"(a2), "r"(a3), "l"(db), "r"(scale_d));
}
__device__ __forceinline__ void wgmma_ss_n64_hi(float (&d)[64], uint64_t da, uint64_t db, int scale_d) {
  asm volatile("{\n.reg .pred p;\nsetp.ne.b32 p, %34, 0;\nwgmma.mma_async.sync.aligned.m64n64k16.f32.bf16.bf16 {%0, %1, %2, %3, %4, %5, %6, %7, %8, %9, %10, %11, %12, %13, %14, %15, %16, %17, %18, %19, %20, %21, %22, %23, %24, %25, %26, %27, %28, %29, %30, %31}, %32, %33, p, 1, 1, 0, 1;\n}"
    : "+f"(d[32]), "+f"(d[33]), "+f"(d[34]), "+f"(d[35]), "+f"(d[36]), "+f"(d[37]), "+f"(d[38]), "+f"(d[39]), "+f"(d[40]), "+f"(d[41]), "+f"(d[42]), "+f"(d[43]), "+f"(d[44]), "+f"(d[45]), "+f"(d[46]), "+f"(d[47]), "+f"(d[48]), "+f"(d[49]), "+f"(d[50]), "+f"(d[51]), "+f"(d[52]), "+f"(d[53]), "+f"(d[54]), "+f"(d[55]), "+f"(d[56]), "+f"(d[57]), "+f"(d[58]), "+f"(d[59]), "+f"(d[60]), "+f"(d[61]), "+f"(d[62]), "+f"(d[63])
    : "l"(da), "l"(db), "r"(scale_d));
}


__device__ __forceinline__ uint64_t bdesc(uint32_t addr) {
    uint32_t lo = ((addr & 0x3FFFF) >> 4) | ((8192u >> 4) << 16);
    uint32_t hi = (1024u >> 4) | (1u << 30);
    return ((uint64_t)hi << 32) | lo;
}

__device__ __forceinline__ uint64_t adesc(uint32_t addr) {
    uint32_t lo = ((addr & 0x3FFFF) >> 4) | (1u << 16);
    uint32_t hi = (1024u >> 4) | (1u << 30);
    return ((uint64_t)hi << 32) | lo;
}

struct Ctx {
    uint32_t sb;
    uint32_t s, sprev;
    uint32_t fbits;
    uint32_t wg, warp, lane, tw;
    bool ok;
    uint64_t db;
    uint32_t pend;
};
__device__ __forceinline__ uint32_t park_off(uint32_t w, int c) { return c < 4 ? w * WGR + c * 8192 : RB_OFF + w * 32768 + (c - 4) * 8192; }
__device__ __forceinline__ void publish_staged(Ctx& cx) {
    asm volatile("fence.proxy.async.shared::cta;" ::: "memory");
    __syncwarp();
    if (cx.lane == 0) mbar_arrive(cx.pend);
}
__device__ __forceinline__ float bf_lo(uint32_t v) { return __uint_as_float(v << 16); }
__device__ __forceinline__ float bf_hi(uint32_t v) { return __uint_as_float(v & 0xFFFF0000u); }

__device__ __forceinline__ void load_x(Ctx& cx, int kb, uint32_t* f) {
    const uint32_t xs = cx.sb + park_off(cx.wg, kb);
    const uint32_t row = cx.warp * 16 + (cx.lane & 15);
#pragma unroll
    for (int k = 0; k < 4; k++) {
        const uint32_t ch = 2 * k + (cx.lane >> 4);
        ldsm4(xs + row * 128 + ((ch ^ (row & 7)) << 4), f[4 * k], f[4 * k + 1], f[4 * k + 2], f[4 * k + 3]);
    }
}

__device__ __forceinline__ void mma_first2(Ctx& cx, float (&acc)[64], float (&acc2)[64]) {
    uint32_t a[32];
    const uint32_t bars = cx.sb + BAR_OFF;
    const uint64_t da = adesc(cx.sb + cx.wg * WGR + 32768);
#pragma unroll
    for (int st = 0; st < 18; st++) {
        if (st == 18 - LAG0 && cx.wg == 1) bar_sync<1, 256>();
        const int kb = st >> 1;
        const int fo = 16 * (kb & 1);
        if ((st & 1) == 0) {
            mbar_wait(bars + 8 * (B_XFULL + kb), 0);
            if (kb < 8) load_x(cx, kb, a + fo);
        }
        if (!cx.ok) mbar_wait(bars + 8 * (B_FULL + cx.s), (cx.fbits >> cx.s) & 1);
        cx.fbits ^= 1u << cx.s;
        const uint64_t db = cx.db;
        const uint32_t sn = cx.s == 8 ? 4 : cx.s + 1;
        wg_fence();
#pragma unroll
        for (int k = 0; k < 4; k++) {
            if (k == 2) cx.ok = mbar_test_wait(bars + 8 * (B_FULL + sn), (cx.fbits >> sn) & 1);
            if (k == 3) {
                wg_commit();
                if (st > 0) {
                    wg_wait<1>();
                    if (cx.tw == 0) mbar_arrive(bars + 8 * (B_EMPTY + cx.sprev));
                }
                cx.db = bdesc(cx.sb + RB_OFF + sn * ST);
            }
            if (kb < 8) {
                if (st & 1) wgmma_rs_n128(acc2, a[fo + 4 * k], a[fo + 4 * k + 1], a[fo + 4 * k + 2], a[fo + 4 * k + 3], db + 128 * k, (kb | k) != 0);
                else wgmma_rs_n128(acc, a[fo + 4 * k], a[fo + 4 * k + 1], a[fo + 4 * k + 2], a[fo + 4 * k + 3], db + 128 * k, (kb | k) != 0);
            } else {
                if (st & 1) wgmma_ss_n128(acc2, da + 2 * k, db + 128 * k, 1);
                else wgmma_ss_n128(acc, da + 2 * k, db + 128 * k, 1);
            }
        }
        wg_commit();
        if (st == 17 && cx.wg == 0) bar_arrive<1, 256>();
        if (st == 17) {
            wg_wait<0>();
            if (cx.tw == 0) mbar_arrive(bars + 8 * (B_EMPTY + cx.s));
        }
        cx.sprev = cx.s; cx.s = sn;
    }
}

template <int MODE>
__device__ __forceinline__ void mma_chunk(Ctx& cx, uint32_t (&a)[128], float (&acc)[64], int step) {
    const uint32_t bars = cx.sb + BAR_OFF;
    const uint32_t priv = cx.warp * 2048 + cx.lane * 16;
    const uint64_t da = adesc(cx.sb + cx.wg * WGR + 32768);
#pragma unroll
    for (int kb = 0; kb < 9; kb++) {
        if (kb == 9 - (MODE == 3 ? LAG2 : LAG1) && cx.wg == 1) bar_sync<1, 256>();
        if (MODE == 0 && kb >= 2 && kb < 8) load_x(cx, kb, a + 16 * kb);
        if (!cx.ok) mbar_wait(bars + 8 * (B_FULL + cx.s), (cx.fbits >> cx.s) & 1);
        cx.fbits ^= 1u << cx.s;
        const uint64_t db = cx.db;
        const uint32_t sn = cx.s == 8 ? (MODE == 3 ? 2 : 4) : cx.s + 1;
        if (kb == 0 || MODE == 0) wg_fence();
        if (kb < 8) {
            wgmma_rs_n128(acc, a[16 * kb + 0], a[16 * kb + 1], a[16 * kb + 2], a[16 * kb + 3], db, kb != 0);
            wgmma_rs_n128(acc, a[16 * kb + 4], a[16 * kb + 5], a[16 * kb + 6], a[16 * kb + 7], db + 128, 1);
            cx.ok = mbar_test_wait(bars + 8 * (B_FULL + sn), (cx.fbits >> sn) & 1);
            wgmma_rs_n128(acc, a[16 * kb + 8], a[16 * kb + 9], a[16 * kb + 10], a[16 * kb + 11], db + 256, 1);
        } else {
            wgmma_ss_n128(acc, da, db, 1);
            wgmma_ss_n128(acc, da + 2, db + 128, 1);
            wgmma_ss_n128(acc, da + 4, db + 256, 1);
        }
        wg_commit();
        if (kb > 0) {
            wg_wait<1>();
            if (cx.tw == 0) mbar_arrive(bars + 8 * (B_EMPTY + cx.sprev));
            if (MODE == 2) {
#pragma unroll
                for (int k = 0; k < 4; k++)
                    lds128(cx.sb + park_off(cx.wg, kb - 1) + priv + k * 512, a[16 * (kb - 1) + 4 * k], a[16 * (kb - 1) + 4 * k + 1], a[16 * (kb - 1) + 4 * k + 2], a[16 * (kb - 1) + 4 * k + 3]);
                wg_fence();
            }
        }
        cx.db = bdesc(cx.sb + RB_OFF + sn * ST);
        if (kb < 8) wgmma_rs_n128(acc, a[16 * kb + 12], a[16 * kb + 13], a[16 * kb + 14], a[16 * kb + 15], db + 384, 1);
        else wgmma_ss_n128(acc, da + 6, db + 384, 1);
        wg_commit();
        if (kb == 8 && cx.wg == 0) bar_arrive<1, 256>();
        if (MODE == 3 && kb == 0 && step > 0) publish_staged(cx);
        if (kb == 8) {
            cx.ok = mbar_test_wait(bars + 8 * (B_FULL + sn), (cx.fbits >> sn) & 1);
            if (MODE == 3 && step > 0) mbar_wait(bars + 8 * (B_SFREE + cx.wg), (step - 1) & 1);
            if (MODE == 3 && step == 2) mbar_wait(bars + 8 * (B_LAND + 0), 0);
            wg_wait<0>();
            if (cx.tw == 0) mbar_arrive(bars + 8 * (B_EMPTY + cx.s));
        }
        cx.sprev = cx.s; cx.s = sn;
    }
}

template <bool LAST>
__device__ __forceinline__ void h_epilogue(Ctx& cx, float (&acc)[64], int c) {
    const uint32_t priv = cx.sb + park_off(cx.wg, c) + cx.warp * 2048 + cx.lane * 16;
    const uint32_t row = cx.warp * 16 + (cx.lane & 15);
#pragma unroll
    for (int k = 0; k < 4; k++) {
        uint32_t h0 = reglu2(acc[8 * k + 0], acc[8 * k + 1], acc[32 + 8 * k + 0], acc[32 + 8 * k + 1]);
        uint32_t h1 = reglu2(acc[8 * k + 2], acc[8 * k + 3], acc[32 + 8 * k + 2], acc[32 + 8 * k + 3]);
        uint32_t h2 = reglu2(acc[8 * k + 4], acc[8 * k + 5], acc[32 + 8 * k + 4], acc[32 + 8 * k + 5]);
        uint32_t h3 = reglu2(acc[8 * k + 6], acc[8 * k + 7], acc[32 + 8 * k + 6], acc[32 + 8 * k + 7]);
        if (LAST) {
            const uint32_t ch = 2 * k + (cx.lane >> 4);
            stsm4(cx.sb + cx.wg * WGR + 32768 + row * 128 + ((ch ^ (row & 7)) << 4), h0, h1, h2, h3);
        } else sts128(priv + k * 512, h0, h1, h2, h3);
    }
    if (LAST) asm volatile("fence.proxy.async.shared::cta;" ::: "memory");
}

__device__ __forceinline__ uint32_t lds32(uint32_t addr) { uint32_t v; asm volatile("ld.shared.u32 %0, [%1];" : "=r"(v) : "r"(addr) : "memory"); return v; }
__device__ __forceinline__ uint4 ld_strong(const uint4* p) {
    uint4 v; asm volatile("ld.relaxed.gpu.global.v4.u32 {%0, %1, %2, %3}, [%4];" : "=r"(v.x), "=r"(v.y), "=r"(v.z), "=r"(v.w) : "l"(p) : "memory"); return v;
}
__device__ __forceinline__ void repair_tiles(uint32_t t0, uint32_t t1, int slot, uint32_t tag) {
    uint32_t bid, t;
    asm volatile("mov.u32 %0, %%ctaid.x;" : "=r"(bid));
    asm volatile("mov.u32 %0, %%tid.x;" : "=r"(t));
    const uint4* g = g_part + (size_t)(bid * 6 + slot) * 1024 + (t >> 7) * 512 + (t & 127);
#pragma unroll 1
    for (int i = 0; i < 8; i++) {
        const uint32_t sa = (i & 1 ? t1 : t0) + (i >> 1) * 2048;
        uint4 v = lds128u(sa);
#pragma unroll 1
        for (int it = 0; ((v.x ^ tag) & 1) && it < 1000000; it++) v = ld_strong(g + (i & 1) * 1024 + (i >> 1) * 128);
        v.x = (v.x & ~1u) | tag;
        sts128(sa, v.x, v.y, v.z, v.w);
    }
}
template <int O>
__device__ __forceinline__ uint32_t sum_pass(float (&acc)[64], uint32_t t0, uint32_t t1, uint32_t tag) {
    uint32_t bad = 0;
#pragma unroll
    for (int p = 0; p < 4; p++) {
        const uint4 u = lds128u(t0 + p * 2048), v = lds128u(t1 + p * 2048);
        bad |= (u.x ^ tag) | (v.x ^ tag);
        acc[O + 8 * p + 0] = bf_lo(u.x) + bf_lo(v.x); acc[O + 8 * p + 1] = bf_hi(u.x) + bf_hi(v.x);
        acc[O + 8 * p + 2] = bf_lo(u.y) + bf_lo(v.y); acc[O + 8 * p + 3] = bf_hi(u.y) + bf_hi(v.y);
        acc[O + 8 * p + 4] = bf_lo(u.z) + bf_lo(v.z); acc[O + 8 * p + 5] = bf_hi(u.z) + bf_hi(v.z);
        acc[O + 8 * p + 6] = bf_lo(u.w) + bf_lo(v.w); acc[O + 8 * p + 7] = bf_hi(u.w) + bf_hi(v.w);
    }
    return bad & 1;
}
template <int O>
__device__ __forceinline__ void add_tiles(float (&acc)[64], uint32_t t0, uint32_t t1, int slot, uint32_t tag_addr) {
    const uint32_t tag = lds32(tag_addr);
    while (__builtin_expect(sum_pass<O>(acc, t0, t1, tag), 0)) repair_tiles(t0, t1, slot, tag);
    __syncwarp();
#pragma unroll
    for (int i = 0; i < 32; i++) asm volatile("" : "+f"(acc[O + i]));
}

__device__ __forceinline__ void acc_tiles_hi(float (&acc)[64], uint32_t t0, uint32_t t1, int slot, uint32_t tag_addr) {
    const uint32_t tag = lds32(tag_addr);
    uint4 u[4], v[4];
    while (true) {
        uint32_t bad = 0;
#pragma unroll
        for (int p = 0; p < 4; p++) {
            u[p] = lds128u(t0 + p * 2048); v[p] = lds128u(t1 + p * 2048);
            bad |= (u[p].x ^ tag) | (v[p].x ^ tag);
        }
        if (__builtin_expect(!(bad & 1), 1)) break;
        repair_tiles(t0, t1, slot, tag);
    }
    __syncwarp();
#pragma unroll
    for (int p = 0; p < 4; p++) {
        acc[32 + 8 * p + 0] += bf_lo(u[p].x) + bf_lo(v[p].x); acc[32 + 8 * p + 1] += bf_hi(u[p].x) + bf_hi(v[p].x);
        acc[32 + 8 * p + 2] += bf_lo(u[p].y) + bf_lo(v[p].y); acc[32 + 8 * p + 3] += bf_hi(u[p].y) + bf_hi(v[p].y);
        acc[32 + 8 * p + 4] += bf_lo(u[p].z) + bf_lo(v[p].z); acc[32 + 8 * p + 5] += bf_hi(u[p].z) + bf_hi(v[p].z);
        acc[32 + 8 * p + 6] += bf_lo(u[p].w) + bf_lo(v[p].w); acc[32 + 8 * p + 7] += bf_hi(u[p].w) + bf_hi(v[p].w);
    }
#pragma unroll
    for (int i = 0; i < 32; i++) asm volatile("" : "+f"(acc[32 + i]));
}

template <int KIND>
__device__ __forceinline__ void mma_chunk64(Ctx& cx, uint32_t (&a)[128], float (&acc)[64]) {
    const uint32_t bars = cx.sb + BAR_OFF;
    const uint64_t da = adesc(cx.sb + cx.wg * WGR + 32768);
    if (cx.wg == 1) bar_sync<KIND == 1 ? 1 : 5, 256>();
#pragma unroll
    for (int i = 0; i < 5; i++) {
        if (!cx.ok) mbar_wait(bars + 8 * (B_FULL + cx.s), (cx.fbits >> cx.s) & 1);
        cx.fbits ^= 1u << cx.s;
        const uint64_t db = cx.db;
        const uint32_t sn = cx.s == 8 ? 2 : cx.s + 1;
        cx.db = bdesc(cx.sb + RB_OFF + sn * ST);
        if (i == 0) wg_fence();
        if (i < 4) {
#pragma unroll
            for (int k = 0; k < 8; k++) {
                if (k == 3) cx.ok = mbar_test_wait(bars + 8 * (B_FULL + sn), (cx.fbits >> sn) & 1);
                if (k == 6) {
                    wg_commit();
                    if (i > 0) {
                        wg_wait<1>();
                        if (cx.tw == 0) mbar_arrive(bars + 8 * (B_EMPTY + cx.sprev));
                    }
                }
                if (KIND == 2) wgmma_rs_n64_hi(acc, a[32 * i + 4 * k], a[32 * i + 4 * k + 1], a[32 * i + 4 * k + 2], a[32 * i + 4 * k + 3], db + 128 * k, 1);
                else wgmma_rs_n64_lo(acc, a[32 * i + 4 * k], a[32 * i + 4 * k + 1], a[32 * i + 4 * k + 2], a[32 * i + 4 * k + 3], db + 128 * k, (i | k) != 0);
            }
            wg_commit();
            if (i == STAG64 && cx.wg == 0) bar_arrive<KIND == 1 ? 1 : 5, 256>();
        } else {
#pragma unroll
            for (int k = 0; k < 4; k++) {
                if (KIND == 2) wgmma_ss_n64_hi(acc, da + 2 * k, db + 512 + 128 * k, 1);
                else wgmma_ss_n64_lo(acc, da + 2 * k, db + 512 + 128 * k, 1);
            }
            wg_commit();
            if (KIND != 2) cx.ok = mbar_test_wait(bars + 8 * (B_FULL + sn), (cx.fbits >> sn) & 1);
            if (KIND == 0) {
                mbar_wait(bars + 8 * (B_SFREE + cx.wg), 0);
                mbar_wait(bars + 8 * (B_LAND + 1), 0);
            }
            if (KIND == 1) {
                mbar_wait_cluster(bars + 8 * (B_RFREE + cx.wg), 0);
            }
            if (KIND == 2) {
                wg_wait<1>();
                if (cx.wg == 0) {
                    mbar_wait(bars + 8 * (B_LAND + 2), 0);
                    add_tiles<0>(acc, cx.sb + RB_OFF + cx.tw * 16, cx.sb + RB_OFF + 16384 + cx.tw * 16, 4, cx.sb + TAG_OFF);
                } else {
#pragma unroll
                    for (int jj = 0; jj < 32; jj++) acc[jj] = 0.f;
                }
                mbar_wait_cluster(bars + 8 * (B_RFULL + cx.wg), 0);
#pragma unroll
                for (int jj = 0; jj < 8; jj++) {
                    const float4 n = lds128f(cx.sb + cx.wg * WGR + 16384 + jj * 2048 + cx.tw * 16);
                    acc[4 * jj] += n.x; acc[4 * jj + 1] += n.y; acc[4 * jj + 2] += n.z; acc[4 * jj + 3] += n.w;
                }
            }
            wg_wait<0>();
            if (KIND != 2 && cx.tw == 0) { mbar_arrive(bars + 8 * (B_EMPTY + cx.sprev)); mbar_arrive(bars + 8 * (B_EMPTY + cx.s)); }
        }
        cx.sprev = cx.s; cx.s = sn;
    }
}

template <int O, int STRIDE>
__device__ __forceinline__ void stage_atom(const float (&acc)[64], uint32_t dst, uint32_t tag) {
#pragma unroll
    for (int p = 0; p < 4; p++) {
        const uint32_t lo = (((__float_as_uint(acc[O + 8 * p]) + ((tag ^ 1) << 16)) >> 17) << 1) | tag;
        const uint32_t w0 = (pack_bf16(0.f, acc[O + 8 * p + 1]) & 0xFFFF0000u) | lo;
        sts128(dst + p * STRIDE, w0, pack_bf16(acc[O + 8 * p + 2], acc[O + 8 * p + 3]),
               pack_bf16(acc[O + 8 * p + 4], acc[O + 8 * p + 5]), pack_bf16(acc[O + 8 * p + 6], acc[O + 8 * p + 7]));
    }
}

__global__ void __cluster_dims__(2, 1, 1) __launch_bounds__(NTHREADS, 1)
reglu_ffn_kernel(const __grid_constant__ CUtensorMap mapX, const __grid_constant__ CUtensorMap mapG, const __grid_constant__ CUtensorMap mapU,
                 const __grid_constant__ CUtensorMap mapD, const __grid_constant__ CUtensorMap mapD1,
                 const __nv_bfloat16* __restrict__ wgp, const __nv_bfloat16* __restrict__ wup, const __nv_bfloat16* __restrict__ wd,
                 __nv_bfloat16* __restrict__ out) {
    extern __shared__ uint8_t smem_raw[];
    const uint32_t sb = (smem_u32(smem_raw) + 1023) & ~1023u;
    const uint32_t bars = sb + BAR_OFF;
    const int tid = threadIdx.x;
    const int r = blockIdx.x & 1, q = (blockIdx.x >> 1) & 3, m = blockIdx.x >> 3;
    const int j = 2 * q + r;
    if (tid == 0) {
        const uint32_t xb = bars + 8 * B_XFULL;
        mbar_init(xb, 1);
        mbar_expect_tx(xb, 16384);
        tma_2d(sb, &mapX, xb, 0, m * 128);
#pragma unroll
        for (int i = 0; i < 2; i++) {
            const uint32_t fb = bars + 8 * (B_FULL + 4 + i);
            mbar_init(fb, 1);
            mbar_expect_tx(fb, ST);
            tma_2d(sb + RB_OFF + (4 + i) * ST, &mapG, fb, j * 576 + i * 64, 0);
            tma_2d(sb + RB_OFF + (4 + i) * ST + 8192, &mapU, fb, j * 576 + i * 64, 0);
            if (i == 0) tma_2d(sb + WGR, &mapX, xb, 0, m * 128 + 64);
        }
    }
    if (tid == 32) prefetch_map(&mapG);
    if (tid == 64) prefetch_map(&mapU);
    const uint32_t wg = __shfl_sync(0xffffffffu, tid >> 7, 0);
    const uint32_t wid = __shfl_sync(0xffffffffu, tid >> 5, 0);
    if (wg == 2) asm volatile("setmaxnreg.dec.sync.aligned.u32 56;");
    if ((tid & 31) == 0 && wid > 0) {
#pragma unroll
        for (int i = 0; i < 4; i++) {
            const int u = (wid - 1) * 4 + i;
            const int b = u < 4 ? u : (u < 16 ? u + 2 : u + 3);
            uint32_t cnt = 1;
            if (b >= B_EMPTY && b < B_EMPTY + 9) cnt = 2;
            else if (b >= B_STG && b < B_STG + 8) cnt = 4;
            else if (b == B_LFREE || b == B_PFREE) cnt = 8;
            mbar_init(bars + 8 * b, cnt);
            if ((b >= B_FULL + 6 && b < B_FULL + 9) || (b > B_XFULL && b < B_RFULL + 2)) mbar_expect_tx(bars + 8 * b, 16384);
        }
        asm volatile("fence.mbarrier_init.release.cluster;" ::: "memory");
    }
    __syncthreads();
    asm volatile("barrier.cluster.arrive.relaxed.aligned;" ::: "memory");
    if ((tid >> 5) == 10) {
        asm volatile("barrier.cluster.wait.acquire.aligned;" ::: "memory");
        if (tid == 320) {
#pragma unroll 1
            for (int kb = 1; kb < 9; kb++) {
                tma_2d_mc(sb + (kb < 8 ? park_off(r, kb) : r * WGR + 32768), &mapX, bars + 8 * (B_XFULL + kb), kb * 64, m * 128 + r * 64);
#pragma unroll 1
                for (int st = 2 * kb; st < 2 * kb + 2 && st < 5; st++) {
                    tma_2d(sb + RB_OFF + (4 + st) * ST, &mapG, bars + 8 * (B_FULL + 4 + st), j * 576 + (st & 1) * 64, kb * 64);
                    tma_2d(sb + RB_OFF + (4 + st) * ST + 8192, &mapU, bars + 8 * (B_FULL + 4 + st), j * 576 + (st & 1) * 64, kb * 64);
                }
                if (kb >= 3) __nanosleep(500);
            }
        }
    }
    __syncwarp();
    if (wg != 2) {
        asm volatile("setmaxnreg.inc.sync.aligned.u32 224;");
        Ctx cx;
        cx.sb = sb; cx.s = 4; cx.sprev = 4; cx.fbits = 0; cx.wg = wg; cx.warp = (tid >> 5) & 3; cx.lane = tid & 31; cx.tw = tid & 127; cx.ok = false; cx.db = bdesc(sb + RB_OFF + 4 * ST);
        uint32_t a[128];
        float acc[64];
        {
            float acc2[64];
            mma_first2(cx, acc2, acc);
            uint32_t hp[32];
#pragma unroll
            for (int i = 0; i < 16; i++) {
                hp[16 + i] = reglu2(acc[2 * i], acc[2 * i + 1], acc[32 + 2 * i], acc[33 + 2 * i]);
                hp[i] = reglu2(acc2[2 * i], acc2[2 * i + 1], acc2[32 + 2 * i], acc2[33 + 2 * i]);
            }
#pragma unroll
            for (int i = 0; i < 32; i++) asm volatile("" : "+r"(hp[i]));
            load_x(cx, 0, a);
            load_x(cx, 1, a + 16);
            __syncwarp();
#pragma unroll
            for (int k = 0; k < 8; k++)
                sts128(sb + park_off(wg, k >> 2) + cx.warp * 2048 + cx.lane * 16 + (k & 3) * 512, hp[4 * k], hp[4 * k + 1], hp[4 * k + 2], hp[4 * k + 3]);
        }
        asm volatile("barrier.cluster.wait.acquire.aligned;" ::: "memory");
        mbar_wait(bars + 8 * B_TAG, 0);
        mma_chunk<0>(cx, a, acc, 0);
        h_epilogue<false>(cx, acc, 2);
        for (int c = 3; c < 8; c++) { mma_chunk<1>(cx, a, acc, 0); h_epilogue<false>(cx, acc, c); }
        mma_chunk<2>(cx, a, acc, 0);
        h_epilogue<true>(cx, acc, 8);
        __syncwarp();
        if (cx.lane == 0) mbar_arrive(bars + 8 * B_PFREE);
        const uint32_t stg = sb + wg * WGR + 16384;
        for (int step = 0; step < 3; step++) {
            mma_chunk<3>(cx, a, acc, step);
            const uint32_t tag = lds32(sb + TAG_OFF);
            stage_atom<0, 2048>(acc, stg + cx.tw * 16, tag);
            stage_atom<32, 2048>(acc, stg + 8192 + cx.tw * 16, tag);
            cx.pend = bars + 8 * (B_STG + 2 * step + wg);
            if (step == 2) publish_staged(cx);
        }
        add_tiles<32>(acc, sb + RB_OFF + wg * 8192 + cx.tw * 16, sb + RB_OFF + 16384 + wg * 8192 + cx.tw * 16, 0, sb + TAG_OFF);
        __syncwarp();
        if (cx.lane == 0) mbar_arrive(bars + 8 * B_LFREE);
        mma_chunk64<0>(cx, a, acc);
        stage_atom<0, 512>(acc, stg + cx.warp * 2048 + cx.lane * 16, lds32(sb + TAG_OFF));
        cx.pend = bars + 8 * (B_STG + 6 + wg);
        publish_staged(cx);
        acc_tiles_hi(acc, sb + wg * WGR + cx.tw * 16, sb + wg * WGR + 8192 + cx.tw * 16, 2, sb + TAG_OFF);
        mma_chunk64<1>(cx, a, acc);
        {
            const uint32_t rb = mapa(sb, r ^ 1);
            const uint32_t rbar = rb + BAR_OFF + 8 * (B_RFULL + wg);
#pragma unroll
            for (int jj = 0; jj < 8; jj++)
                st_async4(rb + wg * WGR + 16384 + jj * 2048 + cx.tw * 16, rbar, acc[4 * jj], acc[4 * jj + 1], acc[4 * jj + 2], acc[4 * jj + 3]);
        }
        if (wg == 1) {
            mbar_wait(bars + 8 * (B_LAND + 2), 0);
            acc_tiles_hi(acc, sb + RB_OFF + 8192 + cx.tw * 16, sb + RB_OFF + 16384 + 8192 + cx.tw * 16, 4, sb + TAG_OFF);
        }
        mma_chunk64<2>(cx, a, acc);
        {
            const uint32_t ot = sb + wg * WGR + 32768 + cx.warp * 2048;
            const uint32_t row = cx.lane & 15;
#pragma unroll
            for (int p = 0; p < 4; p++) {
                const uint32_t ch = 2 * p + (cx.lane >> 4);
                stsm4(ot + row * 128 + ((ch ^ (row & 7)) << 4),
                      pack_bf16(acc[32 + 8 * p] + acc[8 * p], acc[33 + 8 * p] + acc[8 * p + 1]), pack_bf16(acc[34 + 8 * p] + acc[8 * p + 2], acc[35 + 8 * p] + acc[8 * p + 3]),
                      pack_bf16(acc[36 + 8 * p] + acc[8 * p + 4], acc[37 + 8 * p] + acc[8 * p + 5]), pack_bf16(acc[38 + 8 * p] + acc[8 * p + 6], acc[39 + 8 * p] + acc[8 * p + 7]));
            }
            __syncwarp();
            const uint32_t rr = cx.lane >> 3, cc = cx.lane & 7;
            uint4* op = reinterpret_cast<uint4*>(out + (size_t)(m * 128 + wg * 64 + cx.warp * 16 + rr) * D_DIM + j * 64 + cc * 8);
#pragma unroll
            for (int i = 0; i < 4; i++) {
                const uint32_t rw = rr + 4 * i;
                op[i * 4 * (D_DIM / 8)] = lds128u(ot + rw * 128 + ((cc ^ (rw & 7)) << 4));
            }
        }
    } else {
        asm volatile("setmaxnreg.dec.sync.aligned.u32 56;");

        const int hw = (tid >> 5) & 3, lane = tid & 31;
        if (hw == 0) {
            if (lane == 0) {
                prefetch_map(&mapD); prefetch_map(&mapD1);
                uint32_t s = 4, ebits = 0;
                int c = 1, kb = 2;
#pragma unroll 1
                for (int it = 5; it < 81; it++) {
                    mbar_wait(bars + 8 * (B_EMPTY + s), (ebits >> s) & 1);
                    ebits ^= 1u << s;
                    const uint32_t fb = bars + 8 * (B_FULL + s);
                    mbar_expect_tx(fb, ST);
                    tma_2d(sb + RB_OFF + s * ST, &mapG, fb, j * 576 + c * 64, kb * 64);
                    if (it < 17) { c ^= 1; kb += c ^ 1; } else if (++kb == 9) { kb = 0; c++; }
                    s = s == 8 ? 4 : s + 1;
                }
#pragma unroll 1
                for (int step = 0; step < 3; step++) {
                    const int ch = (q + 1 + step) & 3;
#pragma unroll 1
                    for (kb = 0; kb < 9; kb++) {
                        if (step == 0 && s < 4) mbar_wait(bars + 8 * B_PFREE, 0);
                        else {
                            mbar_wait(bars + 8 * (B_EMPTY + s), (ebits >> s) & 1);
                            ebits ^= 1u << s;
                        }
                        const uint32_t fb = bars + 8 * (B_FULL + s);
                        mbar_expect_tx(fb, ST);
                        tma_3d(sb + RB_OFF + s * ST, &mapD, fb, 0, j * 576 + kb * 64, ch * 2);
                        s = s == 8 ? 2 : s + 1;
                    }
                }
#pragma unroll 1
                for (int kind = 0; kind < 3; kind++) {
                    const int col = kind == 0 ? 512 : q * 128 + (kind == 1 ? (r ^ 1) : r) * 64;
#pragma unroll 1
                    for (int i = 0; i < 5; i++) {
                        mbar_wait(bars + 8 * (B_EMPTY + s), (ebits >> s) & 1);
                        ebits ^= 1u << s;
                        const uint32_t fb = bars + 8 * (B_FULL + s);
                        mbar_expect_tx(fb, ST);
                        tma_2d(sb + RB_OFF + s * ST, &mapD1, fb, col, j * 576 + (i < 4 ? i * 128 : 448));
                        s = s == 8 ? 2 : s + 1;
                    }
                }
            }
            __syncwarp();
            asm volatile("barrier.cluster.wait.acquire.aligned;" ::: "memory");
        } else if (hw == 1) {
            if (lane == 0) {
                uint32_t s = 4, ebits = 0;
                int c = 1, kb = 2;
#pragma unroll 1
                for (int it = 5; it < 81; it++) {
                    mbar_wait(bars + 8 * (B_EMPTY + s), (ebits >> s) & 1);
                    ebits ^= 1u << s;
                    tma_2d(sb + RB_OFF + s * ST + 8192, &mapU, bars + 8 * (B_FULL + s), j * 576 + c * 64, kb * 64);
                    if (it < 17) { c ^= 1; kb += c ^ 1; } else if (++kb == 9) { kb = 0; c++; }
                    s = s == 8 ? 4 : s + 1;
                }
                mbar_wait(bars + 8 * B_PFREE, 0);
#pragma unroll 1
                for (int ph = 0; ph < 3; ph += 2) {
                    flag_wait_reset(&g_flag[((m * 8 + j) * 4 + ph) * 32], 2);
                    if (ph == 2) mbar_wait(bars + 8 * B_LFREE, 0);
                    asm volatile("fence.proxy.async;" ::: "memory");
                    mbar_expect_tx(bars + 8 * (B_LAND + ph), 32768);
                    bulk_load(sb + RB_OFF, g_part + (size_t)((m * 8 + j) * 6 + 2 * ph) * 1024, 32768, bars + 8 * (B_LAND + ph));
                }
            }
            __syncwarp();
            asm volatile("barrier.cluster.wait.acquire.aligned;" ::: "memory");
        } else if (hw == 2) {
            if (lane == 0) {
                const uint32_t ep = g_epoch[blockIdx.x] + 1;
                g_epoch[blockIdx.x] = ep;
                asm volatile("st.shared.u32 [%0], %1;" ::"r"(sb + TAG_OFF), "r"(ep & 1) : "memory");
                mbar_arrive(bars + 8 * B_TAG);
                mbar_wait(bars + 8 * B_PFREE, 0);
                flag_wait_reset(&g_flag[((m * 8 + j) * 4 + 1) * 32], 2);
                asm volatile("fence.proxy.async;" ::: "memory");
                mbar_expect_tx(bars + 8 * (B_LAND + 1), 32768);
                const uint4* src = g_part + (size_t)((m * 8 + j) * 6 + 2) * 1024;
#pragma unroll 1
                for (int t = 0; t < 4; t++) bulk_load(sb + (t & 1) * WGR + (t >> 1) * 8192, src + t * 512, 8192, bars + 8 * (B_LAND + 1));
                flag_wait_reset(&g_flag[((m * 8 + j) * 4 + 3) * 32], 8);
            }
            __syncwarp();
        } else {
            asm volatile("barrier.cluster.wait.acquire.aligned;" ::: "memory");
            if (lane == 0) {
                tma_prefetch_2d((m & 1) ? &mapU : &mapG, j * 576 + ((m >> 1) & 1) * 64, (2 + (m >> 2)) * 64);
                if (m < 12) tma_prefetch_2d((m & 1) ? &mapU : &mapG, j * 576 + ((m >> 1) & 1) * 64, (6 + (m >> 2)) * 64);
                mbar_wait(bars + 8 * (B_XFULL + 4), 0);
#pragma unroll 1
                for (int i = 0; i < 18; i++) {
                    const size_t o = (size_t)(m * 36 + 2 * i) * F_DIM + j * 576 + 128;
                    l2_prefetch(wgp + o, 896); l2_prefetch(wgp + o + F_DIM, 896);
                    l2_prefetch(wup + o, 896); l2_prefetch(wup + o + F_DIM, 896);
                    __nanosleep(200);
                }
#pragma unroll 1
                for (int i = 0; i < 36; i++) {
                    l2_prefetch(wd + (size_t)(j * 576 + m * 36 + i) * D_DIM, D_DIM * 2);
                    __nanosleep(200);
                }
#pragma unroll 1
                for (int ph = 0; ph < 4; ph++) {
                    const int ch = (q + 1 + ph) & 3;
#pragma unroll 1
                    for (int w = 0; w < 2; w++) {
                        mbar_wait(bars + 8 * (B_STG + 2 * ph + w), 0);
                        const uint32_t st = sb + w * WGR + 16384;
                        if (ph < 3) {
                            uint4* dst = g_part + (size_t)((m * 8 + 2 * ch) * 6 + 2 * ph + r) * 1024 + w * 512;
                            bulk_store(dst, st, 8192);
                            bulk_store(dst + 6 * 1024, st + 8192, 8192);
                        } else {
#pragma unroll 1
                            for (int v = 0; v < 4; v++) bulk_store(g_partE + (size_t)(m * 8 + w * 4 + v) * 1024 + j * 128, st + v * 2048, 2048);
                        }
                        asm volatile("cp.async.bulk.commit_group;" ::: "memory");
                        asm volatile("cp.async.bulk.wait_group.read 0;" ::: "memory");
                        if (ph < 3) mbar_arrive(bars + 8 * (B_SFREE + w));
                        else mbar_arrive_remote(mapa(bars + 8 * (B_RFREE + w), r ^ 1), 1);
                    }
                    asm volatile("cp.async.bulk.wait_group 0;" ::: "memory");
                    if (ph == 3) {
#pragma unroll 1
                        for (int d = 0; d < 8; d++) flag_add(&g_flag[((m * 8 + d) * 4 + 3) * 32]);
                    } else {
                        flag_add(&g_flag[((m * 8 + 2 * ch) * 4 + ph) * 32]);
                        flag_add(&g_flag[((m * 8 + 2 * ch + 1) * 4 + ph) * 32]);
                    }
                }
            }
            __syncwarp();
        }
        {
            bar_sync<6, 128>();
            const uint32_t tag = lds32(sb + TAG_OFF);
#pragma unroll 1
            for (int p = hw; p < 4; p += 4) {
                const uint4* pe = g_partE + (size_t)(m * 8 + j) * 1024 + p * 32 + lane;
                uint4 e[8];
#pragma unroll
                for (int k = 0; k < 8; k++) e[k] = __ldcg(pe + k * 128);
                float t[8];
#pragma unroll
                for (int i = 0; i < 8; i++) t[i] = 0.f;
#pragma unroll
                for (int k = 0; k < 8; k++) {
#pragma unroll 1
                    for (int it = 0; ((e[k].x ^ tag) & 1) && it < 1000000; it++) e[k] = ld_strong(pe + k * 128);
                    t[0] += bf_lo(e[k].x); t[1] += bf_hi(e[k].x); t[2] += bf_lo(e[k].y); t[3] += bf_hi(e[k].y);
                    t[4] += bf_lo(e[k].z); t[5] += bf_hi(e[k].z); t[6] += bf_lo(e[k].w); t[7] += bf_hi(e[k].w);
                }
                __nv_bfloat16* oe = out + (size_t)(m * 128 + j * 16 + (lane >> 2)) * D_DIM + 512 + (lane & 3) * 2 + p * 16;
                *reinterpret_cast<uint32_t*>(oe) = pack_bf16(t[0], t[1]);
                *reinterpret_cast<uint32_t*>(oe + 8 * D_DIM) = pack_bf16(t[2], t[3]);
                *reinterpret_cast<uint32_t*>(oe + 8) = pack_bf16(t[4], t[5]);
                *reinterpret_cast<uint32_t*>(oe + 8 + 8 * D_DIM) = pack_bf16(t[6], t[7]);
            }
        }
    }
}

__device__ __nv_bfloat16 g_h[(size_t)S_LEN * F_DIM];
__global__ void fallback_h(const __nv_bfloat16* __restrict__ x, const __nv_bfloat16* __restrict__ wg, const __nv_bfloat16* __restrict__ wu) {
    const int f = blockIdx.x * blockDim.x + threadIdx.x, s = blockIdx.y;
    float g = 0.f, u = 0.f;
    for (int d = 0; d < D_DIM; d++) {
        const float xv = __bfloat162float(x[s * D_DIM + d]);
        g += xv * __bfloat162float(wg[(size_t)d * F_DIM + f]);
        u += xv * __bfloat162float(wu[(size_t)d * F_DIM + f]);
    }
    const float gb = __bfloat162float(__float2bfloat16(g)), ub = __bfloat162float(__float2bfloat16(u));
    g_h[(size_t)s * F_DIM + f] = __float2bfloat16((gb > 0.f ? gb : 0.f) * ub);
}
__global__ void fallback_o(const __nv_bfloat16* __restrict__ wd, __nv_bfloat16* __restrict__ out) {
    const int d = blockIdx.x * blockDim.x + threadIdx.x, s = blockIdx.y;
    float a = 0.f;
    for (int f = 0; f < F_DIM; f++) a += __bfloat162float(g_h[(size_t)s * F_DIM + f]) * __bfloat162float(wd[(size_t)f * D_DIM + d]);
    out[s * D_DIM + d] = __float2bfloat16(a);
}

typedef CUresult (*EncodeFn)(CUtensorMap*, CUtensorMapDataType, cuuint32_t, void*, const cuuint64_t*, const cuuint64_t*, const cuuint32_t*,
                             const cuuint32_t*, CUtensorMapInterleave, CUtensorMapSwizzle, CUtensorMapL2promotion, CUtensorMapFloatOOBfill);

}

extern "C" void kernel_launch(void* const* d_in, const int* in_sizes, int n_in, void* d_out, int out_size) {
    static int mode = 0;
    static EncodeFn enc = nullptr;
    static CUtensorMap mX, mG, mU, mD, mD1;
    static const void* cached[4] = {nullptr, nullptr, nullptr, nullptr};
    if (mode == 0) {
        void* fn = nullptr;
        cudaDriverEntryPointQueryResult st;
        cudaGetDriverEntryPoint("cuTensorMapEncodeTiled", &fn, cudaEnableDefault, &st);
        enc = (EncodeFn)fn;
        int nclusters = 0;
        if (enc && cudaFuncSetAttribute(reglu_ffn_kernel, cudaFuncAttributeMaxDynamicSharedMemorySize, SMEM_BYTES) == cudaSuccess) {
            cudaLaunchConfig_t cfg = {};
            cfg.gridDim = dim3(128); cfg.blockDim = dim3(NTHREADS); cfg.dynamicSmemBytes = SMEM_BYTES;
            cudaLaunchAttribute at[1];
            at[0].id = cudaLaunchAttributeClusterDimension; at[0].val.clusterDim.x = 2; at[0].val.clusterDim.y = 1; at[0].val.clusterDim.z = 1;
            cfg.attrs = at; cfg.numAttrs = 1;
            if (cudaOccupancyMaxActiveClusters(&nclusters, reglu_ffn_kernel, &cfg) != cudaSuccess) nclusters = 0;
        }
        (void)cudaGetLastError();
        mode = nclusters >= 64 ? 1 : 2;
    }
    const __nv_bfloat16* x = (const __nv_bfloat16*)d_in[0];
    const __nv_bfloat16* wg = (const __nv_bfloat16*)d_in[1];
    const __nv_bfloat16* wu = (const __nv_bfloat16*)d_in[2];
    const __nv_bfloat16* wd = (const __nv_bfloat16*)d_in[3];
    __nv_bfloat16* out = (__nv_bfloat16*)d_out;
    if (mode == 2) {
        fallback_h<<<dim3(F_DIM / 256, S_LEN), 256>>>(x, wg, wu);
        fallback_o<<<dim3(D_DIM / 64, S_LEN), 64>>>(wd, out);
        return;
    }
    if (cached[0] != d_in[0] || cached[1] != d_in[1] || cached[2] != d_in[2] || cached[3] != d_in[3]) {
        const cuuint32_t es[3] = {1, 1, 1};
        auto make = [&](CUtensorMap* mp, void* base, cuuint32_t rank, const cuuint64_t* dims, const cuuint64_t* str, const cuuint32_t* box) {
            enc(mp, CU_TENSOR_MAP_DATA_TYPE_BFLOAT16, rank, base, dims, str, box, es, CU_TENSOR_MAP_INTERLEAVE_NONE, CU_TENSOR_MAP_SWIZZLE_128B,
                CU_TENSOR_MAP_L2_PROMOTION_L2_256B, CU_TENSOR_MAP_FLOAT_OOB_FILL_NONE);
        };
        { const cuuint64_t dims[2] = {D_DIM, S_LEN}, str[1] = {D_DIM * 2}; const cuuint32_t box[2] = {64, 64}; make(&mX, d_in[0], 2, dims, str, box); }
        { const cuuint64_t dims[2] = {F_DIM, D_DIM}, str[1] = {F_DIM * 2}; const cuuint32_t box[2] = {64, 64};
          make(&mG, d_in[1], 2, dims, str, box); make(&mU, d_in[2], 2, dims, str, box); }
        { const cuuint64_t dims[3] = {64, F_DIM, 9}, str[2] = {D_DIM * 2, 128}; const cuuint32_t box[3] = {64, 64, 2}; make(&mD, d_in[3], 3, dims, str, box); }
        { const cuuint64_t dims[2] = {D_DIM, F_DIM}, str[1] = {D_DIM * 2}; const cuuint32_t box[2] = {64, 128}; make(&mD1, d_in[3], 2, dims, str, box); }
        for (int i = 0; i < 4; i++) cached[i] = d_in[i];
    }
    reglu_ffn_kernel<<<128, NTHREADS, SMEM_BYTES>>>(mX, mG, mU, mD, mD1, wg, wu, wd, out);
}
```
